```python
import torch

def _softmax(x, axis=-1):
    return torch.softmax(x, dim=axis)

def _gelu(x):
    return torch.nn.functional.gelu(x, approximate='tanh')

def _silu(x):
    return torch.nn.functional.silu(x)

def _sigmoid(x):
    return torch.sigmoid(x)

def _layernorm(x, axis=-1, eps=1e-05):
    m = x.mean(dim=axis, keepdim=True)
    v = x.var(dim=axis, keepdim=True, unbiased=False)
    return (x - m) / torch.sqrt(v + eps)

def _scatter_add(tgt, idx, src, axis=0):
    return tgt.clone().index_add_(axis, idx, src)

def _segment_sum(src, seg, n):
    out = torch.zeros((n,) + src.shape[1:], dtype=src.dtype)
    return out.index_add_(0, seg, src)

def _pad(x, pw):
    flat = tuple((v for pair in reversed(pw) for v in pair))
    return torch.nn.functional.pad(x, flat)
kernel_name = 'recurrent_scan__spectral_fnet__mixer_gmlp__prompt'

def setup_inputs():

    _w = lambda a: (lambda t: t.to(torch.bfloat16) if t.is_floating_point() else t)(torch.as_tensor(a))

    def _A_setup():
        B, S, D = (1, 2048, 512)
        ns = torch.arange(S)[:, None] * torch.arange(S)[None, :]
        nd = torch.arange(D)[:, None] * torch.arange(D)[None, :]
        Ws_re = torch.cos(-2.0 * torch.pi * ns / S).to(float)
        Ws_im = torch.sin(-2.0 * torch.pi * ns / S).to(float)
        Wd_re = torch.cos(-2.0 * torch.pi * nd / D).to(float)
        Wd_im = torch.sin(-2.0 * torch.pi * nd / D).to(float)
        return {'x': _w((lambda *s: torch.randn(*s, dtype=torch.bfloat16) * 0.05)(B, S, D)), 'dft_seq_re': _w(Ws_re), 'dft_seq_im': _w(Ws_im), 'dft_hid_re': _w(Wd_re), 'dft_hid_im': _w(Wd_im)}
    _A_in = _A_setup()

    def _B_setup():
        B, S, D, F = (1, 2048, 512, 1376)
        Fh = F // 2
        return {'x': _w((lambda *s: torch.randn(*s, dtype=torch.bfloat16) * 0.05)(B, S, D)), 'w_in': _w((lambda *s: torch.randn(*s, dtype=torch.bfloat16) * 0.4)(D, 2 * Fh)), 'w_sp': _w(0.01 * (lambda *s: torch.randn(*s, dtype=torch.bfloat16) * 0.4)(S, S)), 'b_sp': _w(1.0 + 0.01 * (lambda *s: torch.randn(*s, dtype=torch.bfloat16) * 0.05)(S)), 'w_out': _w((lambda *s: torch.randn(*s, dtype=torch.bfloat16) * 0.05)(Fh, D))}
    _B_in = _B_setup()
    return {'A_x': _A_in['x'], 'A_dft_seq_re': _A_in['dft_seq_re'], 'A_dft_seq_im': _A_in['dft_seq_im'], 'A_dft_hid_re': _A_in['dft_hid_re'], 'A_dft_hid_im': _A_in['dft_hid_im'], 'B_x': _B_in['x'], 'B_w_in': _B_in['w_in'], 'B_w_sp': _B_in['w_sp'], 'B_b_sp': _B_in['b_sp'], 'B_w_out': _B_in['w_out']}

def reference(A_x, A_dft_seq_re, A_dft_seq_im, A_dft_hid_re, A_dft_hid_im, B_x, B_w_in, B_w_sp, B_b_sp, B_w_out):

    def _A_ref(x, dft_seq_re, dft_seq_im, dft_hid_re, dft_hid_im):
        a = torch.einsum('bsd,ed->bse', x, dft_hid_re)
        b = torch.einsum('bsd,ed->bse', x, dft_hid_im)
        y = torch.einsum('ts,bse->bte', dft_seq_re, a) - torch.einsum('ts,bse->bte', dft_seq_im, b)
        return y

    def _B_ref(x, w_in, w_sp, b_sp, w_out):
        B, S, D = x.shape
        F = w_in.shape[-1]
        Fh = F // 2
        z = _gelu(torch.einsum('bsd,df->bsf', x, w_in))
        z1 = z[..., :Fh].clone()
        z2 = _layernorm(z[..., Fh:], axis=-1)
        g = torch.einsum('ts,bsf->btf', w_sp, z2) + b_sp[None, :, None]
        return torch.einsum('bsf,fd->bsd', z1 * g, w_out)
    x = A_x
    xn = _layernorm(x, axis=-1)
    s = _A_ref(xn, A_dft_seq_re, A_dft_seq_im, A_dft_hid_re, A_dft_hid_im)
    g = _silu(_B_ref(xn, B_w_in, B_w_sp, B_b_sp, B_w_out))
    return x + s * g
```

```cpp
#include <cuda_runtime.h>
#include <cuda_bf16.h>
#include <cuda.h>
#include <stdint.h>

namespace {

template<int TB> __device__ __forceinline__ void wgmma_n64(float* d, uint64_t da, uint64_t db, int sd) {
  asm volatile("{\n.reg .pred p;\n"
    "setp.ne.b32 p, %34, 0;\n"
    "wgmma.mma_async.sync.aligned.m64n64k16.f32.bf16.bf16 "
    "{%0,%1,%2,%3,%4,%5,%6,%7,%8,%9,%10,%11,%12,%13,%14,%15,%16,%17,%18,%19,%20,%21,%22,%23,%24,%25,%26,%27,%28,%29,%30,%31}, "
    "%32, %33, p, 1, 1, 0, %35;\n}\n"
    : "+f"(d[0]),"+f"(d[1]),"+f"(d[2]),"+f"(d[3]),"+f"(d[4]),"+f"(d[5]),"+f"(d[6]),"+f"(d[7]),"+f"(d[8]),"+f"(d[9]),"+f"(d[10]),"+f"(d[11]),"+f"(d[12]),"+f"(d[13]),"+f"(d[14]),"+f"(d[15]),"+f"(d[16]),"+f"(d[17]),"+f"(d[18]),"+f"(d[19]),"+f"(d[20]),"+f"(d[21]),"+f"(d[22]),"+f"(d[23]),"+f"(d[24]),"+f"(d[25]),"+f"(d[26]),"+f"(d[27]),"+f"(d[28]),"+f"(d[29]),"+f"(d[30]),"+f"(d[31])
    : "l"(da), "l"(db), "r"(sd), "n"(TB));
}
template<int TB> __device__ __forceinline__ void wgmma_n112(float* d, uint64_t da, uint64_t db, int sd) {
  asm volatile("{\n.reg .pred p;\n"
    "setp.ne.b32 p, %58, 0;\n"
    "wgmma.mma_async.sync.aligned.m64n112k16.f32.bf16.bf16 "
    "{%0,%1,%2,%3,%4,%5,%6,%7,%8,%9,%10,%11,%12,%13,%14,%15,%16,%17,%18,%19,%20,%21,%22,%23,%24,%25,%26,%27,%28,%29,%30,%31,%32,%33,%34,%35,%36,%37,%38,%39,%40,%41,%42,%43,%44,%45,%46,%47,%48,%49,%50,%51,%52,%53,%54,%55}, "
    "%56, %57, p, 1, 1, 0, %59;\n}\n"
    : "+f"(d[0]),"+f"(d[1]),"+f"(d[2]),"+f"(d[3]),"+f"(d[4]),"+f"(d[5]),"+f"(d[6]),"+f"(d[7]),"+f"(d[8]),"+f"(d[9]),"+f"(d[10]),"+f"(d[11]),"+f"(d[12]),"+f"(d[13]),"+f"(d[14]),"+f"(d[15]),"+f"(d[16]),"+f"(d[17]),"+f"(d[18]),"+f"(d[19]),"+f"(d[20]),"+f"(d[21]),"+f"(d[22]),"+f"(d[23]),"+f"(d[24]),"+f"(d[25]),"+f"(d[26]),"+f"(d[27]),"+f"(d[28]),"+f"(d[29]),"+f"(d[30]),"+f"(d[31]),"+f"(d[32]),"+f"(d[33]),"+f"(d[34]),"+f"(d[35]),"+f"(d[36]),"+f"(d[37]),"+f"(d[38]),"+f"(d[39]),"+f"(d[40]),"+f"(d[41]),"+f"(d[42]),"+f"(d[43]),"+f"(d[44]),"+f"(d[45]),"+f"(d[46]),"+f"(d[47]),"+f"(d[48]),"+f"(d[49]),"+f"(d[50]),"+f"(d[51]),"+f"(d[52]),"+f"(d[53]),"+f"(d[54]),"+f"(d[55])
    : "l"(da), "l"(db), "r"(sd), "n"(TB));
}
template<int TB> __device__ __forceinline__ void wgmma_n128(float* d, uint64_t da, uint64_t db, int sd) {
  asm volatile("{\n.reg .pred p;\n"
    "setp.ne.b32 p, %66, 0;\n"
    "wgmma.mma_async.sync.aligned.m64n128k16.f32.bf16.bf16 "
    "{%0,%1,%2,%3,%4,%5,%6,%7,%8,%9,%10,%11,%12,%13,%14,%15,%16,%17,%18,%19,%20,%21,%22,%23,%24,%25,%26,%27,%28,%29,%30,%31,%32,%33,%34,%35,%36,%37,%38,%39,%40,%41,%42,%43,%44,%45,%46,%47,%48,%49,%50,%51,%52,%53,%54,%55,%56,%57,%58,%59,%60,%61,%62,%63}, "
    "%64, %65, p, 1, 1, 0, %67;\n}\n"
    : "+f"(d[0]),"+f"(d[1]),"+f"(d[2]),"+f"(d[3]),"+f"(d[4]),"+f"(d[5]),"+f"(d[6]),"+f"(d[7]),"+f"(d[8]),"+f"(d[9]),"+f"(d[10]),"+f"(d[11]),"+f"(d[12]),"+f"(d[13]),"+f"(d[14]),"+f"(d[15]),"+f"(d[16]),"+f"(d[17]),"+f"(d[18]),"+f"(d[19]),"+f"(d[20]),"+f"(d[21]),"+f"(d[22]),"+f"(d[23]),"+f"(d[24]),"+f"(d[25]),"+f"(d[26]),"+f"(d[27]),"+f"(d[28]),"+f"(d[29]),"+f"(d[30]),"+f"(d[31]),"+f"(d[32]),"+f"(d[33]),"+f"(d[34]),"+f"(d[35]),"+f"(d[36]),"+f"(d[37]),"+f"(d[38]),"+f"(d[39]),"+f"(d[40]),"+f"(d[41]),"+f"(d[42]),"+f"(d[43]),"+f"(d[44]),"+f"(d[45]),"+f"(d[46]),"+f"(d[47]),"+f"(d[48]),"+f"(d[49]),"+f"(d[50]),"+f"(d[51]),"+f"(d[52]),"+f"(d[53]),"+f"(d[54]),"+f"(d[55]),"+f"(d[56]),"+f"(d[57]),"+f"(d[58]),"+f"(d[59]),"+f"(d[60]),"+f"(d[61]),"+f"(d[62]),"+f"(d[63])
    : "l"(da), "l"(db), "r"(sd), "n"(TB));
}
template<int TB> __device__ __forceinline__ void wgmma_n176(float* d, uint64_t da, uint64_t db, int sd) {
  asm volatile("{\n.reg .pred p;\n"
    "setp.ne.b32 p, %90, 0;\n"
    "wgmma.mma_async.sync.aligned.m64n176k16.f32.bf16.bf16 "
    "{%0,%1,%2,%3,%4,%5,%6,%7,%8,%9,%10,%11,%12,%13,%14,%15,%16,%17,%18,%19,%20,%21,%22,%23,%24,%25,%26,%27,%28,%29,%30,%31,%32,%33,%34,%35,%36,%37,%38,%39,%40,%41,%42,%43,%44,%45,%46,%47,%48,%49,%50,%51,%52,%53,%54,%55,%56,%57,%58,%59,%60,%61,%62,%63,%64,%65,%66,%67,%68,%69,%70,%71,%72,%73,%74,%75,%76,%77,%78,%79,%80,%81,%82,%83,%84,%85,%86,%87}, "
    "%88, %89, p, 1, 1, 0, %91;\n}\n"
    : "+f"(d[0]),"+f"(d[1]),"+f"(d[2]),"+f"(d[3]),"+f"(d[4]),"+f"(d[5]),"+f"(d[6]),"+f"(d[7]),"+f"(d[8]),"+f"(d[9]),"+f"(d[10]),"+f"(d[11]),"+f"(d[12]),"+f"(d[13]),"+f"(d[14]),"+f"(d[15]),"+f"(d[16]),"+f"(d[17]),"+f"(d[18]),"+f"(d[19]),"+f"(d[20]),"+f"(d[21]),"+f"(d[22]),"+f"(d[23]),"+f"(d[24]),"+f"(d[25]),"+f"(d[26]),"+f"(d[27]),"+f"(d[28]),"+f"(d[29]),"+f"(d[30]),"+f"(d[31]),"+f"(d[32]),"+f"(d[33]),"+f"(d[34]),"+f"(d[35]),"+f"(d[36]),"+f"(d[37]),"+f"(d[38]),"+f"(d[39]),"+f"(d[40]),"+f"(d[41]),"+f"(d[42]),"+f"(d[43]),"+f"(d[44]),"+f"(d[45]),"+f"(d[46]),"+f"(d[47]),"+f"(d[48]),"+f"(d[49]),"+f"(d[50]),"+f"(d[51]),"+f"(d[52]),"+f"(d[53]),"+f"(d[54]),"+f"(d[55]),"+f"(d[56]),"+f"(d[57]),"+f"(d[58]),"+f"(d[59]),"+f"(d[60]),"+f"(d[61]),"+f"(d[62]),"+f"(d[63]),"+f"(d[64]),"+f"(d[65]),"+f"(d[66]),"+f"(d[67]),"+f"(d[68]),"+f"(d[69]),"+f"(d[70]),"+f"(d[71]),"+f"(d[72]),"+f"(d[73]),"+f"(d[74]),"+f"(d[75]),"+f"(d[76]),"+f"(d[77]),"+f"(d[78]),"+f"(d[79]),"+f"(d[80]),"+f"(d[81]),"+f"(d[82]),"+f"(d[83]),"+f"(d[84]),"+f"(d[85]),"+f"(d[86]),"+f"(d[87])
    : "l"(da), "l"(db), "r"(sd), "n"(TB));
}
template<int TB> __device__ __forceinline__ void wgmma_n256(float* d, uint64_t da, uint64_t db, int sd) {
  asm volatile("{\n.reg .pred p;\n"
    "setp.ne.b32 p, %130, 0;\n"
    "wgmma.mma_async.sync.aligned.m64n256k16.f32.bf16.bf16 "
    "{%0,%1,%2,%3,%4,%5,%6,%7,%8,%9,%10,%11,%12,%13,%14,%15,%16,%17,%18,%19,%20,%21,%22,%23,%24,%25,%26,%27,%28,%29,%30,%31,%32,%33,%34,%35,%36,%37,%38,%39,%40,%41,%42,%43,%44,%45,%46,%47,%48,%49,%50,%51,%52,%53,%54,%55,%56,%57,%58,%59,%60,%61,%62,%63,%64,%65,%66,%67,%68,%69,%70,%71,%72,%73,%74,%75,%76,%77,%78,%79,%80,%81,%82,%83,%84,%85,%86,%87,%88,%89,%90,%91,%92,%93,%94,%95,%96,%97,%98,%99,%100,%101,%102,%103,%104,%105,%106,%107,%108,%109,%110,%111,%112,%113,%114,%115,%116,%117,%118,%119,%120,%121,%122,%123,%124,%125,%126,%127}, "
    "%128, %129, p, 1, 1, 0, %131;\n}\n"
    : "+f"(d[0]),"+f"(d[1]),"+f"(d[2]),"+f"(d[3]),"+f"(d[4]),"+f"(d[5]),"+f"(d[6]),"+f"(d[7]),"+f"(d[8]),"+f"(d[9]),"+f"(d[10]),"+f"(d[11]),"+f"(d[12]),"+f"(d[13]),"+f"(d[14]),"+f"(d[15]),"+f"(d[16]),"+f"(d[17]),"+f"(d[18]),"+f"(d[19]),"+f"(d[20]),"+f"(d[21]),"+f"(d[22]),"+f"(d[23]),"+f"(d[24]),"+f"(d[25]),"+f"(d[26]),"+f"(d[27]),"+f"(d[28]),"+f"(d[29]),"+f"(d[30]),"+f"(d[31]),"+f"(d[32]),"+f"(d[33]),"+f"(d[34]),"+f"(d[35]),"+f"(d[36]),"+f"(d[37]),"+f"(d[38]),"+f"(d[39]),"+f"(d[40]),"+f"(d[41]),"+f"(d[42]),"+f"(d[43]),"+f"(d[44]),"+f"(d[45]),"+f"(d[46]),"+f"(d[47]),"+f"(d[48]),"+f"(d[49]),"+f"(d[50]),"+f"(d[51]),"+f"(d[52]),"+f"(d[53]),"+f"(d[54]),"+f"(d[55]),"+f"(d[56]),"+f"(d[57]),"+f"(d[58]),"+f"(d[59]),"+f"(d[60]),"+f"(d[61]),"+f"(d[62]),"+f"(d[63]),"+f"(d[64]),"+f"(d[65]),"+f"(d[66]),"+f"(d[67]),"+f"(d[68]),"+f"(d[69]),"+f"(d[70]),"+f"(d[71]),"+f"(d[72]),"+f"(d[73]),"+f"(d[74]),"+f"(d[75]),"+f"(d[76]),"+f"(d[77]),"+f"(d[78]),"+f"(d[79]),"+f"(d[80]),"+f"(d[81]),"+f"(d[82]),"+f"(d[83]),"+f"(d[84]),"+f"(d[85]),"+f"(d[86]),"+f"(d[87]),"+f"(d[88]),"+f"(d[89]),"+f"(d[90]),"+f"(d[91]),"+f"(d[92]),"+f"(d[93]),"+f"(d[94]),"+f"(d[95]),"+f"(d[96]),"+f"(d[97]),"+f"(d[98]),"+f"(d[99]),"+f"(d[100]),"+f"(d[101]),"+f"(d[102]),"+f"(d[103]),"+f"(d[104]),"+f"(d[105]),"+f"(d[106]),"+f"(d[107]),"+f"(d[108]),"+f"(d[109]),"+f"(d[110]),"+f"(d[111]),"+f"(d[112]),"+f"(d[113]),"+f"(d[114]),"+f"(d[115]),"+f"(d[116]),"+f"(d[117]),"+f"(d[118]),"+f"(d[119]),"+f"(d[120]),"+f"(d[121]),"+f"(d[122]),"+f"(d[123]),"+f"(d[124]),"+f"(d[125]),"+f"(d[126]),"+f"(d[127])
    : "l"(da), "l"(db), "r"(sd), "n"(TB));
}
template<int TB> __device__ __forceinline__ void wgmma_rs_n128(float* d, uint4 a, uint64_t db, int sd) {
  asm volatile("{\n.reg .pred p;\n"
    "setp.ne.b32 p, %69, 0;\n"
    "wgmma.mma_async.sync.aligned.m64n128k16.f32.bf16.bf16 "
    "{%0,%1,%2,%3,%4,%5,%6,%7,%8,%9,%10,%11,%12,%13,%14,%15,%16,%17,%18,%19,%20,%21,%22,%23,%24,%25,%26,%27,%28,%29,%30,%31,%32,%33,%34,%35,%36,%37,%38,%39,%40,%41,%42,%43,%44,%45,%46,%47,%48,%49,%50,%51,%52,%53,%54,%55,%56,%57,%58,%59,%60,%61,%62,%63}, "
    "{%64,%65,%66,%67}, %68, p, 1, 1, %70;\n}\n"
    : "+f"(d[0]),"+f"(d[1]),"+f"(d[2]),"+f"(d[3]),"+f"(d[4]),"+f"(d[5]),"+f"(d[6]),"+f"(d[7]),"+f"(d[8]),"+f"(d[9]),"+f"(d[10]),"+f"(d[11]),"+f"(d[12]),"+f"(d[13]),"+f"(d[14]),"+f"(d[15]),"+f"(d[16]),"+f"(d[17]),"+f"(d[18]),"+f"(d[19]),"+f"(d[20]),"+f"(d[21]),"+f"(d[22]),"+f"(d[23]),"+f"(d[24]),"+f"(d[25]),"+f"(d[26]),"+f"(d[27]),"+f"(d[28]),"+f"(d[29]),"+f"(d[30]),"+f"(d[31]),"+f"(d[32]),"+f"(d[33]),"+f"(d[34]),"+f"(d[35]),"+f"(d[36]),"+f"(d[37]),"+f"(d[38]),"+f"(d[39]),"+f"(d[40]),"+f"(d[41]),"+f"(d[42]),"+f"(d[43]),"+f"(d[44]),"+f"(d[45]),"+f"(d[46]),"+f"(d[47]),"+f"(d[48]),"+f"(d[49]),"+f"(d[50]),"+f"(d[51]),"+f"(d[52]),"+f"(d[53]),"+f"(d[54]),"+f"(d[55]),"+f"(d[56]),"+f"(d[57]),"+f"(d[58]),"+f"(d[59]),"+f"(d[60]),"+f"(d[61]),"+f"(d[62]),"+f"(d[63])
    : "r"(a.x), "r"(a.y), "r"(a.z), "r"(a.w), "l"(db), "r"(sd), "n"(TB));
}
template<int TB> __device__ __forceinline__ void wgmma_rs_n176(float* d, uint4 a, uint64_t db, int sd) {
  asm volatile("{\n.reg .pred p;\n"
    "setp.ne.b32 p, %93, 0;\n"
    "wgmma.mma_async.sync.aligned.m64n176k16.f32.bf16.bf16 "
    "{%0,%1,%2,%3,%4,%5,%6,%7,%8,%9,%10,%11,%12,%13,%14,%15,%16,%17,%18,%19,%20,%21,%22,%23,%24,%25,%26,%27,%28,%29,%30,%31,%32,%33,%34,%35,%36,%37,%38,%39,%40,%41,%42,%43,%44,%45,%46,%47,%48,%49,%50,%51,%52,%53,%54,%55,%56,%57,%58,%59,%60,%61,%62,%63,%64,%65,%66,%67,%68,%69,%70,%71,%72,%73,%74,%75,%76,%77,%78,%79,%80,%81,%82,%83,%84,%85,%86,%87}, "
    "{%88,%89,%90,%91}, %92, p, 1, 1, %94;\n}\n"
    : "+f"(d[0]),"+f"(d[1]),"+f"(d[2]),"+f"(d[3]),"+f"(d[4]),"+f"(d[5]),"+f"(d[6]),"+f"(d[7]),"+f"(d[8]),"+f"(d[9]),"+f"(d[10]),"+f"(d[11]),"+f"(d[12]),"+f"(d[13]),"+f"(d[14]),"+f"(d[15]),"+f"(d[16]),"+f"(d[17]),"+f"(d[18]),"+f"(d[19]),"+f"(d[20]),"+f"(d[21]),"+f"(d[22]),"+f"(d[23]),"+f"(d[24]),"+f"(d[25]),"+f"(d[26]),"+f"(d[27]),"+f"(d[28]),"+f"(d[29]),"+f"(d[30]),"+f"(d[31]),"+f"(d[32]),"+f"(d[33]),"+f"(d[34]),"+f"(d[35]),"+f"(d[36]),"+f"(d[37]),"+f"(d[38]),"+f"(d[39]),"+f"(d[40]),"+f"(d[41]),"+f"(d[42]),"+f"(d[43]),"+f"(d[44]),"+f"(d[45]),"+f"(d[46]),"+f"(d[47]),"+f"(d[48]),"+f"(d[49]),"+f"(d[50]),"+f"(d[51]),"+f"(d[52]),"+f"(d[53]),"+f"(d[54]),"+f"(d[55]),"+f"(d[56]),"+f"(d[57]),"+f"(d[58]),"+f"(d[59]),"+f"(d[60]),"+f"(d[61]),"+f"(d[62]),"+f"(d[63]),"+f"(d[64]),"+f"(d[65]),"+f"(d[66]),"+f"(d[67]),"+f"(d[68]),"+f"(d[69]),"+f"(d[70]),"+f"(d[71]),"+f"(d[72]),"+f"(d[73]),"+f"(d[74]),"+f"(d[75]),"+f"(d[76]),"+f"(d[77]),"+f"(d[78]),"+f"(d[79]),"+f"(d[80]),"+f"(d[81]),"+f"(d[82]),"+f"(d[83]),"+f"(d[84]),"+f"(d[85]),"+f"(d[86]),"+f"(d[87])
    : "r"(a.x), "r"(a.y), "r"(a.z), "r"(a.w), "l"(db), "r"(sd), "n"(TB));
}

__device__ __align__(1024) uint8_t g_ab[2 * 32 * 4 * 16384];
__device__ __align__(1024) uint8_t g_z2[32 * 4 * 24576];
__device__ __align__(1024) uint4 g_u[64 * 11 * 256];
__device__ __align__(1024) uint4 g_yp[64 * 2 * 8 * 256];
__device__ __align__(128) uint2 g_rs[2048];
__device__ __align__(128) uint32_t g_cs[4 * 2432];
__device__ __align__(128) uint2 g_ln2[2048 * 4];
__device__ __align__(128) uint32_t g_fab[2 * 32 * 4];
__device__ __align__(128) uint32_t g_fz2[4 * 32];
__device__ __align__(128) uint32_t g_epoch[128];
#define PROF_T2(i) do {} while (0)
#define PROF_W0() do {} while (0)
#define PROF_W1(a) do {} while (0)
#define PROF_V(i, v) do {} while (0)
#define PROF_T(i) do {} while (0)
#define PROF_DECL(v) do {} while (0)

struct alignas(64) Params {
  CUtensorMap mX, mX64, mHre, mHim, mWin, mSre, mSim, mWsp, mWout, mOut;
  const __nv_bfloat16 *x, *hre, *him, *win, *bsp, *wout;
  uint8_t cmap[64];
};

constexpr uint32_t SMEM_TOTAL = 232448;
constexpr uint32_t A_STG = 49152, A_STAGING = 196608;
constexpr uint32_t B_STG = 40960, B_R = 163840, B_SPARE = 212992;
constexpr uint32_t MISC = 229376;
constexpr uint32_t BAR_FULL = MISC, BAR_EMPTY = MISC + 32, BAR_XFULL = MISC + 64, BAR_STQ = MISC + 128, BAR_Z1 = MISC + 160,
                   BAR_GELU = MISC + 168, BAR_STGFREE = MISC + 176, BAR_RFREE = MISC + 184, BAR_EXT = MISC + 192, BAR_PUB = MISC + 200,
                   BAR_F1 = MISC + 208;
constexpr uint32_t OFF_RS = MISC + 336, A_EXT = MISC + 1024;
#define PF_DIST 8
#define TICK1 0
#define TICK2 0
#define WAIT_ALL 0
#define CMAP 1
#define PRO_T 2
#define ROT_MASK 12
#define LOADS_FIRST 1
#define GATE_T 5
constexpr int SPIN_LIMIT = 1 << 22;

__device__ __forceinline__ void spin_guard(int n) {
  asm volatile("{\n.reg .pred q;\n.reg .u64 z;\nmov.u64 z, 0;\nsetp.gt.s32 q, %0, %1;\n@q st.global.u32 [z], %0;\n}\n" ::"r"(n), "n"(SPIN_LIMIT) : "memory");
}
template <int Q> __device__ __forceinline__ void tick_align() {
  if (Q) {
    uint32_t t0, t;
    asm volatile("mov.u32 %0, %%globaltimer_lo;" : "=r"(t0));
    do { asm volatile("mov.u32 %0, %%globaltimer_lo;" : "=r"(t)); } while (((t ^ t0) & ~(uint32_t)(Q - 1)) == 0);
  }
}
__device__ __forceinline__ void mbar_init(uint32_t bar, uint32_t cnt) { asm volatile("mbarrier.init.shared::cta.b64 [%0], %1;" ::"r"(bar), "r"(cnt) : "memory"); }
__device__ __forceinline__ void mbar_expect_tx(uint32_t bar, uint32_t tx) { asm volatile("mbarrier.arrive.expect_tx.shared::cta.b64 _, [%0], %1;" ::"r"(bar), "r"(tx) : "memory"); }
__device__ __forceinline__ void mbar_arrive(uint32_t bar) { asm volatile("mbarrier.arrive.shared::cta.b64 _, [%0];" ::"r"(bar) : "memory"); }
__device__ __forceinline__ void mbar_arrive_n(uint32_t bar, uint32_t n) { asm volatile("mbarrier.arrive.shared::cta.b64 _, [%0], %1;" ::"r"(bar), "r"(n) : "memory"); }
__device__ __forceinline__ bool mbar_try(uint32_t bar, uint32_t par) {
  uint32_t ok;
  asm volatile("{\n.reg .pred p;\nmbarrier.try_wait.parity.shared::cta.b64 p, [%1], %2;\nselp.u32 %0, 1, 0, p;\n}\n" : "=r"(ok) : "r"(bar), "r"(par) : "memory");
  return ok;
}
__device__ __forceinline__ bool mbar_test(uint32_t bar, uint32_t par) {
  uint32_t ok;
  asm volatile("{\n.reg .pred p;\nmbarrier.test_wait.parity.shared::cta.b64 p, [%1], %2;\nselp.u32 %0, 1, 0, p;\n}\n" : "=r"(ok) : "r"(bar), "r"(par) : "memory");
  return __shfl_sync(0xffffffffu, ok, 0);
}
__device__ __forceinline__ void mbar_wait(uint32_t bar, uint32_t par) {
  int n = 0;
  while (!mbar_try(bar, par)) { spin_guard(++n); }
}
__device__ __forceinline__ void tma_2d(uint32_t dst, const CUtensorMap* m, int c0, int c1, uint32_t bar) {
  asm volatile("cp.async.bulk.tensor.2d.shared::cluster.global.mbarrier::complete_tx::bytes [%0], [%1, {%3, %4}], [%2];"
               ::"r"(dst), "l"(m), "r"(bar), "r"(c0), "r"(c1) : "memory");
}
__device__ __forceinline__ void tma_2d_mc(uint32_t dst, const CUtensorMap* m, int c0, int c1, uint32_t bar) {
  asm volatile("cp.async.bulk.tensor.2d.shared::cluster.global.mbarrier::complete_tx::bytes.multicast::cluster [%0], [%1, {%3, %4}], [%2], %5;"
               ::"r"(dst), "l"(m), "r"(bar), "r"(c0), "r"(c1), "h"((uint16_t)3) : "memory");
}
__device__ __forceinline__ void release(uint32_t bar, int lane, uint32_t n) {
  if (lane < 2)
    asm volatile("{\n.reg .b32 ra;\nmapa.shared::cluster.u32 ra, %0, %1;\nmbarrier.arrive.shared::cluster.b64 _, [ra], %2;\n}\n" ::"r"(bar), "r"(lane), "r"(n) : "memory");
}
__device__ __forceinline__ void cluster_arrive() { asm volatile("barrier.cluster.arrive.relaxed.aligned;" ::: "memory"); }
__device__ __forceinline__ void cluster_wait() { asm volatile("barrier.cluster.wait.acquire.aligned;" ::: "memory"); }
__device__ __forceinline__ void tma_store_2d(const CUtensorMap* m, int c0, int c1, uint32_t src) {
  asm volatile("cp.async.bulk.tensor.2d.global.shared::cta.bulk_group [%0, {%2, %3}], [%1];" ::"l"(m), "r"(src), "r"(c0), "r"(c1) : "memory");
}
__device__ __forceinline__ void tma_prefetch_2d(const CUtensorMap* m, int c0, int c1) {
  asm volatile("cp.async.bulk.prefetch.tensor.2d.L2.global [%0, {%1, %2}];" ::"l"(m), "r"(c0), "r"(c1) : "memory");
}
__device__ __forceinline__ void bulk_prefetch(const void* src, uint32_t bytes) { asm volatile("cp.async.bulk.prefetch.L2.global [%0], %1;" ::"l"(src), "r"(bytes) : "memory"); }
__device__ __forceinline__ void prefetch_map(const CUtensorMap* m) { asm volatile("prefetch.tensormap [%0];" ::"l"(m) : "memory"); }
__device__ __forceinline__ void bulk_g2s(uint32_t dst, const void* src, uint32_t bytes, uint32_t bar) {
  asm volatile("cp.async.bulk.shared::cluster.global.mbarrier::complete_tx::bytes [%0], [%1], %2, [%3];" ::"r"(dst), "l"(src), "r"(bytes), "r"(bar) : "memory");
}
__device__ __forceinline__ void bulk_g2s_mc(uint32_t dst, const void* src, uint32_t bytes, uint32_t bar) {
  asm volatile("cp.async.bulk.shared::cluster.global.mbarrier::complete_tx::bytes.multicast::cluster [%0], [%1], %2, [%3], %4;" ::"r"(dst), "l"(src), "r"(bytes), "r"(bar), "h"((uint16_t)3) : "memory");
}
__device__ __forceinline__ void bulk_s2g(void* dst, uint32_t src, uint32_t bytes) {
  asm volatile("cp.async.bulk.global.shared::cta.bulk_group [%0], [%1], %2;" ::"l"(dst), "r"(src), "r"(bytes) : "memory");
}
__device__ __forceinline__ void bulk_commit() { asm volatile("cp.async.bulk.commit_group;" ::: "memory"); }
__device__ __forceinline__ void bulk_wait_read() { asm volatile("cp.async.bulk.wait_group.read 0;" ::: "memory"); }
__device__ __forceinline__ void bulk_wait_all() { asm volatile("cp.async.bulk.wait_group 0;" ::: "memory"); }
__device__ __forceinline__ void fence_async_smem() { asm volatile("fence.proxy.async.shared::cta;" ::: "memory"); }
__device__ __forceinline__ void fence_async_global() { asm volatile("fence.proxy.async.global;" ::: "memory"); }
__device__ __forceinline__ void wg_fence() { asm volatile("wgmma.fence.sync.aligned;" ::: "memory"); }
__device__ __forceinline__ void wg_commit() { asm volatile("wgmma.commit_group.sync.aligned;" ::: "memory"); }
template <int N> __device__ __forceinline__ void wg_wait() { asm volatile("wgmma.wait_group.sync.aligned %0;" ::"n"(N) : "memory"); }
__device__ __forceinline__ void bar_sync(int id, int n) { asm volatile("bar.sync %0, %1;" ::"r"(id), "r"(n) : "memory"); }
__device__ __forceinline__ void bar_arrive(int id, int n) { asm volatile("bar.arrive %0, %1;" ::"r"(id), "r"(n) : "memory"); }
__device__ __forceinline__ uint64_t desc_k(uint32_t addr) {
  return (uint64_t)((addr & 0x3FFFF) >> 4) | (1ull << 16) | (64ull << 32) | (1ull << 62);
}
__device__ __forceinline__ uint64_t desc_n(uint32_t addr) {
  return (uint64_t)((addr & 0x3FFFF) >> 4) | (512ull << 16) | (64ull << 32) | (1ull << 62);
}
__device__ __forceinline__ uint64_t desc_ext(uint32_t addr) {
  return (uint64_t)((addr & 0x3FFFF) >> 4) | (8ull << 32);
}
__device__ __forceinline__ void stsm4(uint32_t a, uint32_t r0, uint32_t r1, uint32_t r2, uint32_t r3) {
  asm volatile("stmatrix.sync.aligned.m8n8.x4.shared.b16 [%0], {%1,%2,%3,%4};" ::"r"(a), "r"(r0), "r"(r1), "r"(r2), "r"(r3) : "memory");
}
__device__ __forceinline__ void stsm4t(uint32_t a, uint32_t r0, uint32_t r1, uint32_t r2, uint32_t r3) {
  asm volatile("stmatrix.sync.aligned.m8n8.x4.trans.shared.b16 [%0], {%1,%2,%3,%4};" ::"r"(a), "r"(r0), "r"(r1), "r"(r2), "r"(r3) : "memory");
}
__device__ __forceinline__ void ldsm4(uint32_t a, uint32_t& r0, uint32_t& r1, uint32_t& r2, uint32_t& r3) {
  asm volatile("ldmatrix.sync.aligned.m8n8.x4.shared.b16 {%0,%1,%2,%3}, [%4];" : "=r"(r0), "=r"(r1), "=r"(r2), "=r"(r3) : "r"(a) : "memory");
}
__device__ __forceinline__ uint32_t pack2(float lo, float hi) {
  uint32_t r; asm("cvt.rn.bf16x2.f32 %0, %1, %2;" : "=r"(r) : "f"(hi), "f"(lo)); return r;
}
__device__ __forceinline__ float bf_lo(uint32_t v) { return __uint_as_float(v << 16); }
__device__ __forceinline__ float bf_hi(uint32_t v) { return __uint_as_float(v & 0xFFFF0000u); }
__device__ __forceinline__ float round_bf(float v) { return bf_lo(pack2(v, 0.f)); }
__device__ __forceinline__ float2 lds64(uint32_t a) { float2 v; asm volatile("ld.shared.v2.f32 {%0,%1}, [%2];" : "=f"(v.x), "=f"(v.y) : "r"(a) : "memory"); return v; }
__device__ __forceinline__ float lds32(uint32_t a) { float v; asm volatile("ld.shared.f32 %0, [%1];" : "=f"(v) : "r"(a) : "memory"); return v; }
__device__ __forceinline__ uint32_t lds32u(uint32_t a) { uint32_t v; asm volatile("ld.shared.b32 %0, [%1];" : "=r"(v) : "r"(a) : "memory"); return v; }
__device__ __forceinline__ void sts32(uint32_t a, float v) { asm volatile("st.shared.f32 [%0], %1;" ::"r"(a), "f"(v) : "memory"); }
__device__ __forceinline__ void sts64u(uint32_t a, uint32_t x, uint32_t y) { asm volatile("st.shared.v2.b32 [%0], {%1,%2};" ::"r"(a), "r"(x), "r"(y) : "memory"); }
__device__ __forceinline__ uint4 lds128(uint32_t a) { uint4 v; asm volatile("ld.shared.v4.b32 {%0,%1,%2,%3}, [%4];" : "=r"(v.x), "=r"(v.y), "=r"(v.z), "=r"(v.w) : "r"(a) : "memory"); return v; }
__device__ __forceinline__ void sts128(uint32_t a, uint4 v) { asm volatile("st.shared.v4.b32 [%0], {%1,%2,%3,%4};" ::"r"(a), "r"(v.x), "r"(v.y), "r"(v.z), "r"(v.w) : "memory"); }
__device__ __forceinline__ uint32_t ld_rlx(const uint32_t* p) { uint32_t v; asm volatile("ld.relaxed.gpu.global.b32 %0, [%1];" : "=r"(v) : "l"(p) : "memory"); return v; }
__device__ __forceinline__ uint32_t ld_acq(const uint32_t* p) { uint32_t v; asm volatile("ld.acquire.gpu.global.b32 %0, [%1];" : "=r"(v) : "l"(p) : "memory"); return v; }
__device__ __forceinline__ uint2 ld_rlx2(const uint2* p) { uint2 v; asm volatile("ld.relaxed.gpu.global.v2.b32 {%0,%1}, [%2];" : "=r"(v.x), "=r"(v.y) : "l"(p) : "memory"); return v; }
__device__ __forceinline__ uint4 ld_rlx4(const uint4* p) { uint4 v; asm volatile("ld.relaxed.gpu.global.v4.b32 {%0,%1,%2,%3}, [%4];" : "=r"(v.x), "=r"(v.y), "=r"(v.z), "=r"(v.w) : "l"(p) : "memory"); return v; }
__device__ __forceinline__ void st_rlx(uint32_t* p, uint32_t v) { asm volatile("st.relaxed.gpu.global.b32 [%0], %1;" ::"l"(p), "r"(v) : "memory"); }
__device__ __forceinline__ void st_rel(uint32_t* p, uint32_t v) { asm volatile("st.release.gpu.global.b32 [%0], %1;" ::"l"(p), "r"(v) : "memory"); }
__device__ __forceinline__ void st_rlx2(uint2* p, uint32_t x, uint32_t y) { asm volatile("st.relaxed.gpu.global.v2.b32 [%0], {%1,%2};" ::"l"(p), "r"(x), "r"(y) : "memory"); }
__device__ __forceinline__ void st_rlx4(uint4* p, uint32_t x, uint32_t y, uint32_t z, uint32_t w) { asm volatile("st.relaxed.gpu.global.v4.b32 [%0], {%1,%2,%3,%4};" ::"l"(p), "r"(x), "r"(y), "r"(z), "r"(w) : "memory"); }
__device__ __forceinline__ uint4 ldg128(const void* p) { uint4 v; asm volatile("ld.global.nc.v4.b32 {%0,%1,%2,%3}, [%4];" : "=r"(v.x), "=r"(v.y), "=r"(v.z), "=r"(v.w) : "l"(p)); return v; }
__device__ __forceinline__ uint32_t tagf(float v, uint32_t par) { return (__float_as_uint(v) & ~1u) | par; }
__device__ __forceinline__ float tanh_fast(float v) { float r; asm("tanh.approx.f32 %0, %1;" : "=f"(r) : "f"(v)); return r; }
__device__ __forceinline__ float gelu_h(float h) {
  const float u = h * fmaf(h * h, 8.f * 0.7978845608f * 0.044715f, 2.f * 0.7978845608f);
  return fmaf(h, tanh_fast(u), h);
}
__device__ __forceinline__ float silu_f(float v) { const float h = 0.5f * v; return fmaf(h, tanh_fast(h), h); }
__device__ __forceinline__ uint32_t bmul2(uint32_t a, uint32_t b) { uint32_t r; asm("mul.rn.bf16x2 %0, %1, %2;" : "=r"(r) : "r"(a), "r"(b)); return r; }
__device__ __forceinline__ uint32_t badd2(uint32_t a, uint32_t b) { uint32_t r; asm("add.rn.bf16x2 %0, %1, %2;" : "=r"(r) : "r"(a), "r"(b)); return r; }
__device__ __forceinline__ uint32_t bfma2(uint32_t a, uint32_t b, uint32_t c) { uint32_t r; asm("fma.rn.bf16x2 %0, %1, %2, %3;" : "=r"(r) : "r"(a), "r"(b), "r"(c)); return r; }
__device__ __forceinline__ float sum8(uint4 v) {
  return ((bf_lo(v.x) + bf_hi(v.x)) + (bf_lo(v.y) + bf_hi(v.y))) + ((bf_lo(v.z) + bf_hi(v.z)) + (bf_lo(v.w) + bf_hi(v.w)));
}
__device__ __forceinline__ void acc_sq(uint4 v, float& s, float& q) {
  const float a0 = bf_lo(v.x), a1 = bf_hi(v.x), a2 = bf_lo(v.y), a3 = bf_hi(v.y), a4 = bf_lo(v.z), a5 = bf_hi(v.z), a6 = bf_lo(v.w), a7 = bf_hi(v.w);
  s += ((a0 + a1) + (a2 + a3)) + ((a4 + a5) + (a6 + a7));
  q += fmaf(a0, a0, fmaf(a1, a1, fmaf(a2, a2, a3 * a3))) + fmaf(a4, a4, fmaf(a5, a5, fmaf(a6, a6, a7 * a7)));
}
template <int N> __device__ __forceinline__ void zero_acc(float* a) {
#pragma unroll
  for (int i = 0; i < N; i++) a[i] = 0.f;
}
__device__ __forceinline__ float rcp_fast(float v) { float r; asm("rcp.approx.ftz.f32 %0, %1;" : "=f"(r) : "f"(v)); return r; }
__device__ __forceinline__ float std_ref(float var) {
  float s;
  asm("sqrt.approx.ftz.f32 %0, %1;" : "=f"(s) : "f"(round_bf(round_bf(fmaxf(var, 0.f)) + 1e-5f)));
  return s;
}
__device__ __forceinline__ float rstd_ref(float var) { return rcp_fast(round_bf(std_ref(var))); }
__device__ __forceinline__ float rs_rstd(uint32_t w) { return rcp_fast(__uint_as_float((w & 0x7FFFu) << 16)); }
__device__ __forceinline__ uint4 ext_frag(uint32_t r0, uint32_t r1, int i4, int w) {
  const uint32_t n0 = (r0 >> 16) ^ 0x8000u, n1 = (r1 >> 16) ^ 0x8000u;
  const uint32_t mul = i4 == 2 * w ? 0x10001u : i4 == 2 * w + 1 ? 1u : 0u;
  return make_uint4(n0 * mul, n1 * mul, 0, 0);
}

__device__ __forceinline__ uint32_t load_epoch() { return ld_rlx(&g_epoch[blockIdx.x]) + 1; }
__device__ __forceinline__ void wait_flags(uint32_t& mask, uint32_t need, const uint32_t* f, uint32_t epoch) {
  if ((mask & need) == need) return;
  int n = 0;
  while (true) {
    mask = __ballot_sync(0xffffffffu, ld_acq(f) == epoch);
    if ((mask & need) == need) break;
    spin_guard(++n);
  }
  __syncwarp();
  fence_async_global();
}
__device__ __forceinline__ void publish(uint32_t* f, uint32_t epoch) { st_rel(f, epoch); }

__device__ __forceinline__ void prep(const Params& p, uint32_t sb, uint32_t red0, int tid) {
  const int bid = blockIdx.x, wq = tid >> 5, lane = tid & 31, g = lane >> 2, i4 = lane & 3;
  uint4 X[8], H[4], W[8];
  {
    const __nv_bfloat16* xr = p.x + (size_t)(bid * 16 + wq * 4 + (lane >> 3)) * 512 + (lane & 7) * 8;
    const int hr = bid * 8 + g;
    const __nv_bfloat16* hp = (hr < 512 ? p.hre : p.him) + (size_t)(hr & 511) * 512 + wq * 128 + i4 * 8;
    const int col = (bid % 22) * 64 + g * 8;
    const bool dow = bid < 88 && col < 1376;
    const __nv_bfloat16* wp = p.win + (size_t)((bid / 22) * 128 + wq * 32 + i4) * 1376 + col;
#pragma unroll
    for (int t = 0; t < 8; t++) X[t] = ldg128(xr + t * 64);
#pragma unroll
    for (int t = 0; t < 4; t++) H[t] = ldg128(hp + t * 32);
#pragma unroll
    for (int t = 0; t < 8; t++) W[t] = dow ? ldg128(wp + t * 4 * 1376) : make_uint4(0, 0, 0, 0);
  }
  const uint32_t par = load_epoch() & 1u;
  {
    float s = 0.f, q = 0.f;
#pragma unroll
    for (int t = 0; t < 8; t++) acc_sq(X[t], s, q);
#pragma unroll
    for (int o = 1; o < 8; o <<= 1) { s += __shfl_xor_sync(0xffffffffu, s, o); q += __shfl_xor_sync(0xffffffffu, q, o); }
    const float m = s * (1.f / 512.f);
    const uint32_t wd = pack2(std_ref(fmaf(q, 1.f / 512.f, -m * m)), m) | (par << 15);
    if ((lane & 7) == 0) st_rlx2(&g_rs[bid * 16 + wq * 4 + (lane >> 3)], wd, wd);
  }
  if (tid == 0 && false) PROF_T(7);
  {
    float sh = (sum8(H[0]) + sum8(H[1])) + (sum8(H[2]) + sum8(H[3]));
    sh += __shfl_xor_sync(0xffffffffu, sh, 1); sh += __shfl_xor_sync(0xffffffffu, sh, 2);
    if (i4 == 0) st_rlx(&g_cs[wq * 2432 + bid * 8 + g], tagf(sh, par));
  }
  if (tid == 0 && false) PROF_T(16);
  if (bid < 88) {
    const bool u1 = i4 & 1, u2 = i4 & 2;
    float c[8];
    c[0] = bf_lo(W[0].x); c[1] = bf_hi(W[0].x); c[2] = bf_lo(W[0].y); c[3] = bf_hi(W[0].y);
    c[4] = bf_lo(W[0].z); c[5] = bf_hi(W[0].z); c[6] = bf_lo(W[0].w); c[7] = bf_hi(W[0].w);
#pragma unroll
    for (int t = 1; t < 8; t++) {
      c[0] += bf_lo(W[t].x); c[1] += bf_hi(W[t].x); c[2] += bf_lo(W[t].y); c[3] += bf_hi(W[t].y);
      c[4] += bf_lo(W[t].z); c[5] += bf_hi(W[t].z); c[6] += bf_lo(W[t].w); c[7] += bf_hi(W[t].w);
    }
#pragma unroll
    for (int k = 0; k < 4; k++) c[k] = (u2 ? c[k + 4] : c[k]) + __shfl_xor_sync(0xffffffffu, u2 ? c[k] : c[k + 4], 2);
#pragma unroll
    for (int k = 0; k < 2; k++) c[k] = (u1 ? c[k + 2] : c[k]) + __shfl_xor_sync(0xffffffffu, u1 ? c[k] : c[k + 2], 1);
    sts64u(red0 + wq * 256 + lane * 8, __float_as_uint(c[0]), __float_as_uint(c[1]));
    bar_sync(3, 128);
    if (tid < 64) {
      const uint32_t a = red0 + tid * 4;
      st_rlx(&g_cs[(bid / 22) * 2432 + 1024 + (bid % 22) * 64 + tid], tagf((lds32(a) + lds32(a + 256)) + (lds32(a + 512) + lds32(a + 768)), par));
    }
  }
  __syncwarp();
  if (lane == 0) mbar_arrive(sb + BAR_PUB);
  if (tid == 0) PROF_T(29);
}
__device__ __forceinline__ void gather(uint32_t sb, uint32_t ext, int ht, uint32_t epoch, int rb, int c0a, int c0b, int ncol) {
  const uint32_t par = epoch & 1u;
  const int e = ht * 4, set = e >= ncol, col = set ? e - ncol : e;
  const bool on = e < 2 * ncol;
  const uint4* cp = (const uint4*)&g_cs[on ? (set ? c0b : c0a) + col : c0a];
  const uint4* rp = (const uint4*)&g_rs[rb * 128 + (ht & 63) * 2];
  mbar_wait(sb + BAR_PUB, 0);
  mbar_wait(sb + BAR_F1 + GATE_T * 8, 0);
  if (ht == 0 && false) PROF_T(19);
  uint4 rs, v0, v1, v2, v3;
  int n = 0;
  while (true) {
    rs = ld_rlx4(rp); v0 = ld_rlx4(cp); v1 = ld_rlx4(cp + 608); v2 = ld_rlx4(cp + 1216); v3 = ld_rlx4(cp + 1824);
    if (!((((rs.x >> 15) ^ par) | (v0.x ^ par) | (v1.x ^ par) | (v2.x ^ par) | (v3.x ^ par)) & 1u)) break;
    spin_guard(++n);
  }
  if (ht == 0 && false) PROF_V(20, n * 1000);
  if (ht < 64) sts64u(sb + OFF_RS + ht * 8, rs.x, rs.z);
  if (on) {
    const float s[4] = {(__uint_as_float(v0.x) + __uint_as_float(v1.x)) + (__uint_as_float(v2.x) + __uint_as_float(v3.x)),
                        (__uint_as_float(v0.y) + __uint_as_float(v1.y)) + (__uint_as_float(v2.y) + __uint_as_float(v3.y)),
                        (__uint_as_float(v0.z) + __uint_as_float(v1.z)) + (__uint_as_float(v2.z) + __uint_as_float(v3.z)),
                        (__uint_as_float(v0.w) + __uint_as_float(v1.w)) + (__uint_as_float(v2.w) + __uint_as_float(v3.w))};
#pragma unroll
    for (int k = 0; k < 4; k++) {
      const float hi = round_bf(s[k]), mid = round_bf(s[k] - hi);
      sts64u(ext + (col + k) * 16 + set * 8, pack2(hi, mid), pack2(s[k] - hi - mid, 0.f));
    }
  }
  fence_async_smem();
  mbar_arrive(sb + BAR_EXT);
  __syncwarp();
  if (ht == 0) PROF_T(11);
}

template <int N, class F> __device__ __forceinline__ void recv_issue(const uint4* src, F off, uint4* v) {
#pragma unroll
  for (int i = 0; i < N; i++) v[i] = ld_rlx4(src + off(i));
}
template <int N, class F> __device__ __forceinline__ void recv_finish(const uint4* src, F off, uint32_t par, uint4* v) {
  int n = 0;
  while (true) {
    uint32_t bad = 0;
#pragma unroll
    for (int i = 0; i < N; i++) bad |= v[i].x ^ par;
    if (!(bad & 1u)) break;
    spin_guard(++n);
    recv_issue<N>(src, off, v);
  }
  __syncwarp();
}
__device__ __forceinline__ void send_y(uint4* dst, uint32_t par, const float* acc) {
#pragma unroll
  for (int i = 0; i < 8; i++) {
    const float* a = acc + 8 * i;
    st_rlx4(dst + i * 256, (pack2(a[0], a[1]) & ~1u) | par, pack2(a[2], a[3]), pack2(a[4], a[5]), pack2(a[6], a[7]));
  }
}
template <int N> __device__ __forceinline__ void retuple(float* a) {
#pragma unroll
  for (int i = 0; i < N; i++) asm volatile("mov.b32 %0, %1;" : "=f"(a[i]) : "f"(a[i]));
}

__device__ __forceinline__ void prod_A(const Params& p, uint32_t sb, int pair, int rank) {
  const int c = (pair >> 1) & 1, h = pair & 1, rb = (pair >> 2) * 2 + rank, q = 2 * c + h;
  const int wq = threadIdx.x >> 5, lane = threadIdx.x & 31;
  if (wq == 0) {
    cluster_wait();
    if (lane == 0) {
#pragma unroll 1
      for (int t = 4; t < 16; t++) {
        const int s = t & 3;
        mbar_wait(sb + BAR_EMPTY + s * 8, ((t >> 2) & 1) ^ 1);
        mbar_expect_tx(sb + BAR_F1 + t * 8, 16384);
        tma_2d_mc(sb + s * A_STG + 32768 + rank * 8192, t < 8 ? &p.mHre : &p.mHim, (t & 7) * 64, q * 128 + rank * 64, sb + BAR_F1 + t * 8);
      }
    }
    __syncwarp();
    const uint32_t epoch = load_epoch();
    const int qq = 2 * c + (h ^ 1 ^ rank);
    uint32_t mask = 0;
#pragma unroll 1
    for (int n = 0; n < 32; n++) {
      const int s = n & 3, r = n >> 4, kb = 16 * h + 2 * (n & 7) + ((n >> 3) & 1);
      if (lane == 0) {
        mbar_wait(sb + BAR_EMPTY + s * 8, ((n >> 2) & 1) ^ 1);
        mbar_expect_tx(sb + BAR_FULL + s * 8, A_STG);
        tma_2d(sb + s * A_STG, r ? &p.mSim : &p.mSre, kb * 64, rb * 128, sb + BAR_FULL + s * 8);
      }
      __syncwarp();
      wait_flags(mask, 1u << n, &g_fab[(lane >> 3) * 64 + (8 * h + (lane & 7)) * 4 + qq], epoch);
      if (n == 0 && lane == 0) PROF_T(8);
      if (lane == 0) bulk_g2s_mc(sb + s * A_STG + 16384 + rank * 16384, g_ab + (size_t)((r * 32 + kb) * 4 + qq) * 16384, 16384, sb + BAR_FULL + s * 8);
    }
  } else {
    cluster_wait();
    const uint32_t epoch = load_epoch();
    gather(sb, sb + A_EXT, threadIdx.x - 32, epoch, rb, q * 128, 512 + q * 128, 128);
    if (wq <= 2 && lane == 0) {
      const int mb = wq - 1;
#pragma unroll 1
      for (int r = 0; r < 2; r++) {
        mbar_wait(sb + BAR_STQ + (r * 2 + mb) * 8, 0);
        bulk_s2g(g_ab + (size_t)((r * 32 + 2 * rb + mb) * 4 + q) * 16384, sb + A_STAGING + mb * 16384, 16384);
        bulk_commit();
        bulk_wait_all();
        if (r == 0) mbar_arrive(sb + BAR_STGFREE);
        if (r == 0 && mb == 0) PROF_T(22);
        publish(&g_fab[(r * 2 + mb) * 64 + rb * 4 + q], epoch);
        if (mb == 0) PROF_T(9 + r);
      }
    }
  }
}

__device__ __forceinline__ void cons_A(const Params& p, uint32_t sb, int pair, int rank) {
  const int c = (pair >> 1) & 1, h = pair & 1, rb = (pair >> 2) * 2 + rank, q = 2 * c + h;
  const int w = __shfl_sync(0xffffffffu, (int)(threadIdx.x >> 7) - 1, 0), tid = threadIdx.x & 127, wq = tid >> 5, lane = tid & 31;
  const uint64_t dk0 = desc_k(sb), dn0 = desc_n(sb);
  {
    float acc[128];
    zero_acc<128>(acc);
    PROF_DECL(wt1);
#pragma unroll 1
    for (int i = 0; i < 8; i++) {
      PROF_W0();
      if (i == 0 && tid == 0 && w == 0) PROF_T(27);
      mbar_wait(sb + BAR_XFULL + i * 8, 0);
      if (i == 0 && tid == 0 && w == 0) PROF_T(28);
      mbar_wait(sb + BAR_F1 + (w * 8 + i) * 8, 0);
      if (i > 0) PROF_W1(wt1);
      if (i == 0 && tid == 0) PROF_T(1 + w);
      if (i == 7 && tid == 0) { PROF_T(32 + w); PROF_V(34 + w, wt1); }
      const uint64_t da = dk0 + (i >> 1) * (A_STG >> 4) + (i & 1) * 1024, db = dk0 + (i & 3) * (A_STG >> 4) + 2048;
      wg_fence();
#pragma unroll
      for (int k = 0; k < 4; k++) {
        wgmma_n128<0>(acc, da + 2 * k, db + 2 * k, 1);
        wgmma_n128<0>(acc + 64, da + 512 + 2 * k, db + 2 * k, 1);
      }
      wg_commit();
      wg_wait<1>();
      if (i > 0) release(sb + BAR_EMPTY + ((i - 1) & 3) * 8, lane, 2);
    }
    wg_wait<0>();
    release(sb + BAR_EMPTY + 3 * 8, lane, 2);
    mbar_wait(sb + BAR_EXT, 0);
    uint32_t rs[4];
#pragma unroll
    for (int i = 0; i < 4; i++) rs[i] = lds32u(sb + OFF_RS + ((i >> 1) * 64 + wq * 16 + (lane >> 2) + (i & 1) * 8) * 4);
    {
      const uint4 e0 = ext_frag(rs[0], rs[1], lane & 3, w), e1 = ext_frag(rs[2], rs[3], lane & 3, w);
      wg_fence();
      wgmma_rs_n128<0>(acc, e0, desc_ext(sb + A_EXT), 1); wgmma_rs_n128<0>(acc + 64, e1, desc_ext(sb + A_EXT), 1);
      wg_commit();
      wg_wait<0>();
    }
    if (tid == 0) PROF_T(30 + w);
    if (w) mbar_wait(sb + BAR_STGFREE, 0);
    const uint32_t a0 = sb + A_STAGING + (wq * 16 + (lane & 15)) * 128, sw = (lane >> 4) ^ (lane & 7);
#pragma unroll
    for (int mb = 0; mb < 2; mb++) {
      float r0 = rs_rstd(rs[2 * mb]), r1 = rs_rstd(rs[2 * mb + 1]);
      if (w) { r0 = -r0; r1 = -r1; }
#pragma unroll
      for (int g = 0; g < 16; g += 2) {
        const float* a = acc + mb * 64 + g * 4;
        stsm4(a0 + mb * 16384 + (g >> 3) * 8192 + (((g & 7) ^ sw) << 4), pack2(a[0] * r0, a[1] * r0), pack2(a[2] * r1, a[3] * r1),
              pack2(a[4] * r0, a[5] * r0), pack2(a[6] * r1, a[7] * r1));
      }
      fence_async_smem();
      mbar_arrive(sb + BAR_STQ + (w * 2 + mb) * 8);
    }
    if (tid == 0) PROF_T(3 + w);
  }
  float acc[128];
  zero_acc<128>(acc);
  PROF_DECL(wt2);
#pragma unroll 1
  for (int n = 0; n < 28; n++) {
    const int s = n & 3;
    PROF_W0();
    mbar_wait(sb + BAR_FULL + s * 8, (n >> 2) & 1);
    if (n > 0) PROF_W1(wt2);
    if (n == 0 && tid == 0) PROF_T(5 + w);
    if (n == 27 && tid == 0) { PROF_T(36 + w); PROF_V(38 + w, wt2); }
    if (n == 8 && tid == 0 && w == 0) PROF_T(40);
    if (n == 16 && tid == 0 && w == 0) PROF_T(41);
    const uint64_t da = dk0 + s * (A_STG >> 4) + w * 512, db = dn0 + s * (A_STG >> 4) + 1024;
    wg_fence();
#pragma unroll
    for (int k = 0; k < 4; k++) wgmma_n256<1>(acc, da + 2 * k, db + 128 * k, 1);
    wg_commit();
    wg_wait<1>();
    if (n > 0) release(sb + BAR_EMPTY + ((n - 1) & 3) * 8, lane, 1);
  }
  wg_wait<0>();
  release(sb + BAR_EMPTY + 3 * 8, lane, 1);
  if (tid == 0 && w == 0) PROF_T(42);
  retuple<128>(acc);
  const uint64_t da0 = dk0 + w * 512;
#pragma unroll 1
  for (int s = 0; s < 3; s++) {
    mbar_wait(sb + BAR_FULL + s * 8, 1);
    wg_fence();
#pragma unroll
    for (int k = 0; k < 4; k++) wgmma_n128<1>(acc, da0 + s * (A_STG >> 4) + 2 * k, dn0 + s * (A_STG >> 4) + 1024 + 128 * k, 1);
    wg_commit();
  }
  wg_fence();
#pragma unroll
  for (int k = 0; k < 4; k++) wgmma_n128<1>(acc + 64, da0 + 2 * k, dn0 + 2048 + 128 * k, 1);
  wg_commit();
  if (tid == 0 && w == 0) PROF_T(13);
  mbar_wait(sb + BAR_FULL + 24, 1);
  if (tid == 0 && w == 0) PROF_T(43);
  wg_fence();
#pragma unroll
  for (int k = 0; k < 4; k++) wgmma_n128<1>(acc, da0 + 3 * (A_STG >> 4) + 2 * k, dn0 + 3 * (A_STG >> 4) + 1024 + 128 * k, 1);
  wg_commit();
#pragma unroll
  for (int s = 1; s < 4; s++) {
#pragma unroll
    for (int k = 0; k < 4; k++) wgmma_n128<1>(acc + 64, da0 + s * (A_STG >> 4) + 2 * k, dn0 + s * (A_STG >> 4) + 2048 + 128 * k, 1);
  }
  wg_commit();
  const uint32_t par = load_epoch() & 1u;
  wg_wait<1>();
  if (tid == 0 && w == 0) PROF_T(12);
  send_y(g_yp + (size_t)((rb * 4 + (q ^ 1)) * 2 + h) * 2048 + w * 128 + tid, par, acc);
  wg_wait<0>();
  if (tid == 0) PROF_T(14 + w);
  send_y(g_yp + (size_t)((rb * 4 + q) * 2 + h) * 2048 + w * 128 + tid, par, acc + 64);
  if (tid == 0) PROF_T(17 + w);
}

__device__ __forceinline__ void wout_tile(const Params& p, uint32_t dst, uint32_t bar, int j, int jo, int i, int rank) {
  tma_2d_mc(dst + rank * 8192, &p.mWout, j * 128 + rank * 64, ((j + jo) & 3) * 176 + i * 64, bar);
}
__device__ __forceinline__ void prod_B(const Params& p, uint32_t sb, int pair, int rank) {
  const int rb = (pair >> 2) * 2 + rank, j = pair & 3;
  const int tid = threadIdx.x, wq = tid >> 5, lane = tid & 31;
  if (wq == 0) {
    cluster_wait();
    if (lane == 0) {
#pragma unroll 1
      for (int t = PRO_T; t < 16; t++) {
        const int s = t & 3;
        const uint32_t full = sb + BAR_F1 + t * 8;
        mbar_wait(sb + BAR_EMPTY + s * 8, ((t >> 2) & 1) ^ 1);
        mbar_expect_tx(full, B_STG);
        tma_2d_mc(sb + s * B_STG + rank * 8192, &p.mX64, (t & 7) * 64, rb * 128 + rank * 64, full);
        const int col = (t < 8 ? 688 : 0) + 176 * j;
        tick_align<TICK1>();
#pragma unroll 1
        for (int i = 0; i < 3; i++) tma_2d_mc(sb + s * B_STG + 16384 + i * 8192 + rank * 4096, &p.mWin, col + 64 * i, (t & 7) * 64 + rank * 32, full);
      }
    }
    __syncwarp();
    const uint32_t epoch = load_epoch();
    uint32_t mask = 0;
#pragma unroll 1
    for (int n = 0; n < 32; n++) {
      const int s = n & 3, nr = (n & 16) | ((n + (rb & ROT_MASK)) & 15), kb = 2 * (nr & 15) + (n >> 4);
      const uint32_t full = sb + BAR_FULL + s * 8;
      if (lane == 0) {
        mbar_wait(sb + BAR_EMPTY + s * 8, ((n >> 2) & 1) ^ 1);
        mbar_expect_tx(full, B_STG);
        tma_2d(sb + s * B_STG, &p.mWsp, kb * 64, rb * 128, full);
      }
      __syncwarp();
      wait_flags(mask, 1u << nr, &g_fz2[j * 32 + lane], epoch);
      if (n == 0 && lane == 0) PROF_T(8);
      if (lane == 0) bulk_g2s_mc(sb + s * B_STG + 16384 + rank * 12288, g_z2 + (size_t)(kb * 4 + j) * 24576 + rank * 12288, 12288, full);
    }
    if (lane == 0) {
      mbar_expect_tx(sb + BAR_XFULL, 16384);
      wout_tile(p, sb + B_SPARE, sb + BAR_XFULL, j, 0, 0, rank);
      mbar_wait(sb + BAR_RFREE, 0);
      mbar_expect_tx(sb + BAR_XFULL + 8, 49152);
#pragma unroll 1
      for (int i = 0; i < 3; i++) wout_tile(p, sb + B_R + i * 16384, sb + BAR_XFULL + 8, j, i >> 1, (i + 1) % 3, rank);
#pragma unroll 1
      for (int s = 0; s < 4; s++) {
        const uint32_t full = sb + BAR_FULL + s * 8;
        mbar_wait(sb + BAR_EMPTY + s * 8, 1);
        mbar_expect_tx(full, B_STG);
#pragma unroll 1
        for (int i = 0; i < 2; i++) wout_tile(p, sb + s * B_STG + i * 16384, full, j, s ? s : 2 + i, s ? 1 + i : 0, rank);
        tma_2d(sb + s * B_STG + 32768, &p.mX64, j * 128 + (s & 1) * 64, rb * 128 + (s >> 1) * 64, full);
      }
    }
  } else {
    cluster_wait();
    const uint32_t epoch = load_epoch();
    gather(sb, sb + B_SPARE, tid - 32, epoch, rb, 1024 + 688 + 176 * j, 1024 + 176 * j, 176);
    if (wq <= 2 && lane == 0) {
      const int mb = wq - 1;
      mbar_wait(sb + BAR_STQ + mb * 8, 0);
      uint8_t* dst = g_z2 + (size_t)((2 * rb + mb) * 4 + j) * 24576;
#pragma unroll 1
      for (int i = 0; i < 3; i++) bulk_s2g(dst + i * 8192, sb + B_R + i * 16384 + mb * 8192, 8192);
      bulk_commit();
      bulk_wait_all();
      mbar_arrive(sb + BAR_STGFREE);
      if (mb == 0) PROF_T(22);
      publish(&g_fz2[j * 32 + mb * 16 + rb], epoch);
      PROF_T(mb ? 21 : 9);
    }
    __syncwarp();
    mbar_wait(sb + BAR_Z1, 0);
#pragma unroll 1
    for (int ch = tid - 32; ch < 3072; ch += 96) {
      const uint32_t a = sb + B_R + ch * 16;
      const float hr = 0.5f * rs_rstd(lds32u(sb + OFF_RS + ((ch >> 3) & 127) * 4));
      uint4 v = lds128(a);
      v.x = pack2(gelu_h(hr * bf_lo(v.x)), gelu_h(hr * bf_hi(v.x)));
      v.y = pack2(gelu_h(hr * bf_lo(v.y)), gelu_h(hr * bf_hi(v.y)));
      v.z = pack2(gelu_h(hr * bf_lo(v.z)), gelu_h(hr * bf_hi(v.z)));
      v.w = pack2(gelu_h(hr * bf_lo(v.w)), gelu_h(hr * bf_hi(v.w)));
      sts128(a, v);
    }
    mbar_arrive(sb + BAR_GELU);
    if (tid == 32) PROF_T(10);
  }
}

__device__ __forceinline__ uint4 ufrag(const float* v, const uint32_t* z, uint32_t par) {
  return make_uint4((bmul2(z[0], pack2(v[0], v[1])) & ~1u) | par, bmul2(z[1], pack2(v[2], v[3])), bmul2(z[2], pack2(v[4], v[5])), bmul2(z[3], pack2(v[6], v[7])));
}

__device__ __forceinline__ void cons_B(const Params& p, uint32_t sb, int pair, int rank) {
  const int rb = (pair >> 2) * 2 + rank, j = pair & 3;
  const int w = __shfl_sync(0xffffffffu, (int)(threadIdx.x >> 7) - 1, 0), tid = threadIdx.x & 127, wq = tid >> 5, lane = tid & 31;
  const uint64_t dk0 = desc_k(sb), dn0 = desc_n(sb);
  const uint32_t sw = (lane >> 4) ^ (lane & 7);
  uint32_t par;
  uint16_t bs0, bs1;
  {
    float acc[176];
    zero_acc<176>(acc);
    PROF_DECL(wt1);
#pragma unroll 1
    for (int i = 0; i < 8; i++) {
      PROF_W0();
      mbar_wait(sb + BAR_F1 + (w * 8 + i) * 8, 0);
      if (i > 0) PROF_W1(wt1);
      if (i == 0 && tid == 0) PROF_T(1 + w);
      if (i == 7 && tid == 0) { PROF_T(32 + w); PROF_V(34 + w, wt1); }
      const uint64_t da = dk0 + (i & 3) * (B_STG >> 4), db = dn0 + (i & 3) * (B_STG >> 4) + 1024;
      wg_fence();
#pragma unroll
      for (int k = 0; k < 4; k++) {
        wgmma_n176<1>(acc, da + 2 * k, db + 128 * k, 1);
        wgmma_n176<1>(acc + 88, da + 512 + 2 * k, db + 128 * k, 1);
      }
      wg_commit();
      wg_wait<1>();
      if (i > 0) release(sb + BAR_EMPTY + ((i - 1) & 3) * 8, lane, 2);
    }
    {
      wg_wait<0>();
      release(sb + BAR_EMPTY + 3 * 8, lane, 2);
      mbar_wait(sb + BAR_EXT, 0);
      uint32_t rs[4];
#pragma unroll
      for (int i = 0; i < 4; i++) rs[i] = lds32u(sb + OFF_RS + ((i >> 1) * 64 + wq * 16 + (lane >> 2) + (i & 1) * 8) * 4);
      const uint4 e0 = ext_frag(rs[0], rs[1], lane & 3, w), e1 = ext_frag(rs[2], rs[3], lane & 3, w);
      wg_fence();
      wgmma_rs_n176<0>(acc, e0, desc_ext(sb + B_SPARE), 1); wgmma_rs_n176<0>(acc + 88, e1, desc_ext(sb + B_SPARE), 1);
      wg_commit();
      par = load_epoch() & 1u;
      const uint16_t* bp = (const uint16_t*)p.bsp + rb * 128 + w * 64 + wq * 16 + (lane >> 2);
      asm volatile("ld.global.nc.u16 %0, [%1];" : "=h"(bs0) : "l"(bp));
      asm volatile("ld.global.nc.u16 %0, [%1];" : "=h"(bs1) : "l"(bp + 8));
      wg_wait<0>();
    }
    if (tid == 0) PROF_T(30 + w);
    const uint32_t a0 = sb + B_R + (wq * 16 + (lane & 15)) * 128;
    if (w == 0) {
      const int i4 = lane & 3;
      uint32_t* ex = (uint32_t*)&g_ln2[rb * 512 + wq * 16 + (lane >> 2)];
#pragma unroll 1
      for (int mb = 0; mb < 2; mb++) {
        const float h0 = 0.5f * rs_rstd(lds32u(sb + OFF_RS + (mb * 64 + wq * 16 + (lane >> 2)) * 4)), h1 = 0.5f * rs_rstd(lds32u(sb + OFF_RS + (mb * 64 + wq * 16 + (lane >> 2) + 8) * 4));
        float s0 = 0.f, q0 = 0.f, s1 = 0.f, q1 = 0.f;
        uint32_t z[44];
#pragma unroll
        for (int g = 0; g < 11; g++) {
          float e[8];
#pragma unroll
          for (int k = 0; k < 8; k++) e[k] = gelu_h(acc[g * 8 + k] * ((k & 2) ? h1 : h0));
          s0 += (e[0] + e[1]) + (e[4] + e[5]); s1 += (e[2] + e[3]) + (e[6] + e[7]);
          q0 = fmaf(e[0], e[0], fmaf(e[1], e[1], fmaf(e[4], e[4], fmaf(e[5], e[5], q0))));
          q1 = fmaf(e[2], e[2], fmaf(e[3], e[3], fmaf(e[6], e[6], fmaf(e[7], e[7], q1))));
          z[4 * g] = pack2(e[0], e[1]); z[4 * g + 1] = pack2(e[2], e[3]); z[4 * g + 2] = pack2(e[4], e[5]); z[4 * g + 3] = pack2(e[6], e[7]);
        }
        {
          const bool u1 = i4 & 1, u2 = i4 & 2;
          const float e0 = (u2 ? q0 : s0) + __shfl_xor_sync(0xffffffffu, u2 ? s0 : q0, 2);
          const float e1 = (u2 ? q1 : s1) + __shfl_xor_sync(0xffffffffu, u2 ? s1 : q1, 2);
          st_rlx(ex + (j * 128 + mb * 64 + (i4 & 1) * 8) * 2 + (i4 >> 1), tagf((u1 ? e1 : e0) + __shfl_xor_sync(0xffffffffu, u1 ? e0 : e1, 1), par));
        }
        if (tid == 0) PROF_T(12 + mb);
#pragma unroll
        for (int i = 0; i < 88; i++) acc[i] = acc[88 + i];
        uint2 pa, pb;
        int n = 0;
        while (true) {
          pa = ld_rlx2((const uint2*)ex + i4 * 128 + mb * 64); pb = ld_rlx2((const uint2*)ex + i4 * 128 + mb * 64 + 8);
          if (!(((pa.x ^ par) | (pa.y ^ par) | (pb.x ^ par) | (pb.y ^ par)) & 1u)) break;
          spin_guard(++n);
        }
        __syncwarp();
        float m0 = __uint_as_float(pa.x), m1 = __uint_as_float(pb.x);
        q0 = __uint_as_float(pa.y); q1 = __uint_as_float(pb.y);
#pragma unroll
        for (int o = 1; o < 4; o <<= 1) {
          m0 += __shfl_xor_sync(0xffffffffu, m0, o); q0 += __shfl_xor_sync(0xffffffffu, q0, o);
          m1 += __shfl_xor_sync(0xffffffffu, m1, o); q1 += __shfl_xor_sync(0xffffffffu, q1, o);
        }
        m0 *= (1.f / 688.f); m1 *= (1.f / 688.f);
        const float r0 = rstd_ref(fmaf(q0, 1.f / 688.f, -m0 * m0)), r1 = rstd_ref(fmaf(q1, 1.f / 688.f, -m1 * m1));
        const uint32_t n0 = pack2(-m0, -m0), n1 = pack2(-m1, -m1), c0 = pack2(r0, r0), c1 = pack2(r1, r1);
#pragma unroll
        for (int g = 0; g < 22; g += 2)
          stsm4(a0 + mb * 8192 + (g >> 3) * 16384 + (((g & 7) ^ sw) << 4), bmul2(badd2(z[2 * g], n0), c0), bmul2(badd2(z[2 * g + 1], n1), c1),
                bmul2(badd2(z[2 * g + 2], n0), c0), bmul2(badd2(z[2 * g + 3], n1), c1));
        fence_async_smem();
        mbar_arrive(sb + BAR_STQ + mb * 8);
        if (tid == 0 && mb == 0) PROF_T(20);
      }
    } else {
      mbar_wait(sb + BAR_STGFREE, 0);
#pragma unroll
      for (int g = 0; g < 22; g += 2) {
        const uint32_t ad = a0 + (g >> 3) * 16384 + (((g & 7) ^ sw) << 4);
#pragma unroll
        for (int mb = 0; mb < 2; mb++) {
          const float* a = acc + mb * 88 + g * 4;
          stsm4(ad + mb * 8192, pack2(a[0], a[1]), pack2(a[2], a[3]), pack2(a[4], a[5]), pack2(a[6], a[7]));
        }
      }
      mbar_arrive(sb + BAR_Z1);
    }
  }
  if (tid == 0) PROF_T(3 + w);
  float oc[64];
  uint4* ux = g_u + (size_t)(rb * 4) * 2816 + w * 128 + tid;
  const int o1 = ((j + 1) & 3) * 2816, o2 = ((j + 2) & 3) * 2816, o3 = ((j + 3) & 3) * 2816;
  auto offE = [&](int i) { return (i < 4 ? o1 : i < 8 ? o2 : o3) + (i & 3) * 256; };
  auto offL = [&](int i) { return (i < 7 ? o1 : i < 14 ? o2 : o3) + (4 + i % 7) * 256; };
  uint4 ue[12];
  {
    float acc[88];
    {
      const float b0 = __uint_as_float((uint32_t)bs0 << 16), b1 = __uint_as_float((uint32_t)bs1 << 16);
#pragma unroll
      for (int i = 0; i < 88; i++) asm volatile("mov.b32 %0, %1;" : "=f"(acc[i]) : "f"((i & 2) ? b1 : b0));
    }
    PROF_DECL(wt2);
#pragma unroll 1
    for (int n = 0; n < 28; n++) {
      const int s = n & 3;
      PROF_W0();
      mbar_wait(sb + BAR_FULL + s * 8, (n >> 2) & 1);
      if (n > 0) PROF_W1(wt2);
      if (n == 0 && tid == 0) PROF_T(5 + w);
      if (n == 27 && tid == 0) { PROF_T(36 + w); PROF_V(38 + w, wt2); }
      if (n == 8 && tid == 0 && w == 0) PROF_T(40);
      if (n == 16 && tid == 0 && w == 0) PROF_T(41);
      const uint64_t da = dk0 + s * (B_STG >> 4) + w * 512, db = dn0 + s * (B_STG >> 4) + 1024;
      wg_fence();
#pragma unroll
      for (int k = 0; k < 4; k++) wgmma_n176<1>(acc, da + 2 * k, db + 128 * k, 1);
      wg_commit();
      wg_wait<1>();
      if (n > 0) release(sb + BAR_EMPTY + ((n - 1) & 3) * 8, lane, 1);
    }
    uint32_t z[44];
    {
      mbar_wait(sb + BAR_GELU, 0);
      const uint32_t ua = sb + B_R + (w * 64 + wq * 16 + (lane & 15)) * 128;
#pragma unroll
      for (int g = 0; g < 22; g += 2) ldsm4(ua + (g >> 3) * 16384 + (((g & 7) ^ sw) << 4), z[2 * g], z[2 * g + 1], z[2 * g + 2], z[2 * g + 3]);
      if (j == 3) { z[40] = 0; z[41] = 0; z[42] = 0; z[43] = 0; }
    }
    fence_async_smem();
    __syncwarp();
    release(sb + BAR_RFREE, lane, 1);
    if (tid == 0 && w == 0) PROF_T(42);
    retuple<88>(acc);
    const uint64_t da0 = dk0 + w * 512;
#pragma unroll 1
    for (int s = 0; s < 3; s++) {
      mbar_wait(sb + BAR_FULL + s * 8, 1);
      wg_fence();
#pragma unroll
      for (int k = 0; k < 4; k++) wgmma_n64<1>(acc, da0 + s * (B_STG >> 4) + 2 * k, dn0 + s * (B_STG >> 4) + 1024 + 128 * k, 1);
      wg_commit();
    }
    wg_fence();
#pragma unroll
    for (int s = 0; s < 2; s++) {
#pragma unroll
      for (int k = 0; k < 4; k++) wgmma_n112<1>(acc + 32, da0 + s * (B_STG >> 4) + 2 * k, dn0 + s * (B_STG >> 4) + 1536 + 128 * k, 1);
    }
    wg_commit();
    if (tid == 0 && w == 0) PROF_T(26);
    mbar_wait(sb + BAR_FULL + 24, 1);
    if (tid == 0 && w == 0) PROF_T(43);
    wg_fence();
#pragma unroll
    for (int k = 0; k < 4; k++) wgmma_n64<1>(acc, da0 + 3 * (B_STG >> 4) + 2 * k, dn0 + 3 * (B_STG >> 4) + 1024 + 128 * k, 1);
    wg_commit();
#pragma unroll
    for (int s = 2; s < 4; s++) {
#pragma unroll
      for (int k = 0; k < 4; k++) wgmma_n112<1>(acc + 32, da0 + s * (B_STG >> 4) + 2 * k, dn0 + s * (B_STG >> 4) + 1536 + 128 * k, 1);
    }
    wg_commit();
    wg_wait<2>();
    release(sb + BAR_EMPTY, lane, 1); release(sb + BAR_EMPTY + 8, lane, 1);
    wg_wait<1>();
    if (tid == 0 && w == 0) PROF_T(27);
    uint4 uf[11];
#pragma unroll
    for (int k = 0; k < 4; k++) {
      uf[k] = ufrag(acc + 8 * k, z + 4 * k, par);
      st_rlx4(ux + j * 2816 + k * 256, uf[k].x, uf[k].y, uf[k].z, uf[k].w);
    }
    mbar_wait(sb + BAR_XFULL, 0);
    wg_fence();
#pragma unroll
    for (int k = 0; k < 4; k++) wgmma_rs_n128<1>(oc, uf[k], dn0 + (B_SPARE >> 4) + 128 * k, k);
    wg_commit();
    wg_wait<1>();
    release(sb + BAR_EMPTY + 16, lane, 1); release(sb + BAR_EMPTY + 24, lane, 1);
    if (tid == 0) PROF_T(14 + w);
#pragma unroll
    for (int k = 4; k < 11; k++) {
      uf[k] = ufrag(acc + 8 * k, z + 4 * k, par);
      st_rlx4(ux + j * 2816 + k * 256, uf[k].x, uf[k].y, uf[k].z, uf[k].w);
    }
    recv_issue<12>(ux, offE, ue);
    mbar_wait(sb + BAR_XFULL + 8, 0);
    wg_fence();
#pragma unroll
    for (int k = 4; k < 11; k++) wgmma_rs_n128<1>(oc, uf[k], dn0 + (B_R >> 4) + ((k - 4) >> 2) * 1024 + 128 * (k & 3), 1);
    wg_commit();
  }
  {
    uint4 ul[21];
    recv_finish<12>(ux, offE, par, ue);
    if (tid == 0 && w == 0) PROF_T(16);
    mbar_wait(sb + BAR_FULL, 0);
    wg_fence();
#pragma unroll
    for (int k = 0; k < 12; k++) wgmma_rs_n128<1>(oc, ue[k], dn0 + (k < 4 ? (B_R >> 4) + 2048 : ((k - 4) >> 2) * 1024) + 128 * (k & 3), 1);
    wg_commit();
    wg_wait<1>();
    recv_issue<21>(ux, offL, ul);
    recv_finish<21>(ux, offL, par, ul);
    if (tid == 0 && w == 0) PROF_T(28);
#pragma unroll
    for (int s = 1; s < 4; s++) {
      mbar_wait(sb + BAR_FULL + s * 8, 0);
      wg_fence();
#pragma unroll
      for (int k = 0; k < 7; k++) wgmma_rs_n128<1>(oc, ul[(s - 1) * 7 + k], dn0 + s * (B_STG >> 4) + (k >> 2) * 1024 + 128 * (k & 3), 1);
      wg_commit();
    }
    wg_wait<1>();
  }
  {
    const uint4* ysrc = g_yp + (size_t)(rb * 4 + j) * 4096 + w * 128 + tid;
    auto offY = [](int i) { return i * 256; };
    uint4 y[16];
    recv_issue<16>(ysrc, offY, y);
    const uint32_t a0 = sb + w * 2 * B_STG + 32768 + (wq * 16 + (lane & 15)) * 128;
    uint32_t x[32];
#pragma unroll
    for (int i = 0; i < 8; i++) ldsm4(a0 + (i >> 2) * B_STG + ((((2 * i) & 7) ^ sw) << 4), x[4 * i], x[4 * i + 1], x[4 * i + 2], x[4 * i + 3]);
    wg_wait<0>();
    if (tid == 0 && w == 0) PROF_T(7);
    uint32_t gt[32];
#pragma unroll
    for (int k = 0; k < 32; k++) gt[k] = pack2(silu_f(oc[2 * k]), silu_f(oc[2 * k + 1]));
    if (tid == 0 && w == 0) PROF_T(24);
    recv_finish<16>(ysrc, offY, par, y);
    if (tid == 0 && w == 0) PROF_T(19);
#pragma unroll
    for (int i = 0; i < 8; i++)
      stsm4(a0 + (i >> 2) * B_STG + ((((2 * i) & 7) ^ sw) << 4), bfma2(badd2(y[i].x, y[i + 8].x), gt[4 * i], x[4 * i]),
            bfma2(badd2(y[i].y, y[i + 8].y), gt[4 * i + 1], x[4 * i + 1]), bfma2(badd2(y[i].z, y[i + 8].z), gt[4 * i + 2], x[4 * i + 2]),
            bfma2(badd2(y[i].w, y[i + 8].w), gt[4 * i + 3], x[4 * i + 3]));
    fence_async_smem();
    bar_sync(4 + w, 128);
    if (tid == 0) {
      tma_store_2d(&p.mOut, j * 128, rb * 128 + w * 64, sb + w * 2 * B_STG + 32768);
      tma_store_2d(&p.mOut, j * 128 + 64, rb * 128 + w * 64, sb + (w * 2 + 1) * B_STG + 32768);
      bulk_commit();
      bulk_wait_read();
      PROF_T(17 + w);
    }
  }
}

__global__ void __launch_bounds__(384, 1) fused_kernel(const __grid_constant__ Params p) {
  extern __shared__ __align__(1024) uint8_t smem[];
  const uint32_t sb = (uint32_t)__cvta_generic_to_shared(smem);
  const int cl = p.cmap[blockIdx.x >> 1], rank = blockIdx.x & 1, pair = cl >> 1;
  const bool isA = (cl & 1) == 0;
  if (threadIdx.x == 0) {
    PROF_T(0);
#pragma unroll
    for (int i = 0; i < 8; i++) mbar_init(sb + BAR_XFULL + i * 8, 1);
#pragma unroll
    for (int i = 0; i < 4; i++) mbar_init(sb + BAR_F1 + i * 8, 1);
    asm volatile("fence.mbarrier_init.release.cluster;" ::: "memory");
    fence_async_smem();
    const int rb = (pair >> 2) * 2 + rank;
    if (isA) {
#pragma unroll 1
      for (int t = 0; t < PRO_T; t++) {
        mbar_expect_tx(sb + BAR_XFULL + t * 8, 16384);
        tma_2d(sb + (t >> 1) * A_STG + (t & 1) * 16384, &p.mX, t * 64, rb * 128, sb + BAR_XFULL + t * 8);
        if (t < 4) {
          mbar_expect_tx(sb + BAR_F1 + t * 8, 16384);
          tma_2d(sb + t * A_STG + 32768, &p.mHre, t * 64, (pair & 3) * 128, sb + BAR_F1 + t * 8);
          tma_2d(sb + t * A_STG + 40960, &p.mHre, t * 64, (pair & 3) * 128 + 64, sb + BAR_F1 + t * 8);
        }
      }
    } else {
#pragma unroll 1
      for (int t = 0; t < PRO_T; t++) {
        const uint32_t full = sb + BAR_F1 + t * 8;
        mbar_expect_tx(full, B_STG);
        tma_2d(sb + t * B_STG, &p.mX, t * 64, rb * 128, full);
#pragma unroll 1
        for (int k = 0; k < 6; k++) tma_2d(sb + t * B_STG + 16384 + k * 4096, &p.mWin, 688 + 176 * (pair & 3) + 64 * (k >> 1), t * 64 + (k & 1) * 32, full);
      }
    }
    PROF_T(25);
  } else if (threadIdx.x == 32) {
    spin_guard((sb & 1023) ? SPIN_LIMIT + 1 : 0);
#pragma unroll
    for (int i = 0; i < 4; i++) { mbar_init(sb + BAR_FULL + i * 8, 1); mbar_init(sb + BAR_EMPTY + i * 8, 16); mbar_init(sb + BAR_STQ + i * 8, 128); }
#pragma unroll
    for (int i = 4; i < 16; i++) mbar_init(sb + BAR_F1 + i * 8, 1);
    mbar_init(sb + BAR_Z1, 128); mbar_init(sb + BAR_GELU, 96); mbar_init(sb + BAR_STGFREE, 2); mbar_init(sb + BAR_RFREE, 16);
    mbar_init(sb + BAR_EXT, 96); mbar_init(sb + BAR_PUB, 4);
    asm volatile("fence.mbarrier_init.release.cluster;" ::: "memory");
    fence_async_smem();
  }
  __syncthreads();
  cluster_arrive();
  if (threadIdx.x < 128) {
    asm volatile("setmaxnreg.dec.sync.aligned.u32 40;");
    if (isA) prod_A(p, sb, pair, rank); else prod_B(p, sb, pair, rank);
  } else {
    asm volatile("setmaxnreg.inc.sync.aligned.u32 232;");
    if (threadIdx.x == 128 && isA) PROF_T(26);
    if (threadIdx.x >= 256) prep(p, sb, sb + (isA ? A_STAGING : B_R), threadIdx.x - 256);
    cluster_wait();
    if (isA) cons_A(p, sb, pair, rank); else cons_B(p, sb, pair, rank);
  }
  __syncwarp();
  cluster_arrive();
  cluster_wait();
  if (threadIdx.x == 0) { asm volatile("red.relaxed.gpu.global.add.u32 [%0], 1;" ::"l"(&g_epoch[blockIdx.x]) : "memory"); PROF_T(23); }
}

typedef CUresult (*EncFn)(CUtensorMap*, CUtensorMapDataType, cuuint32_t, void*, const cuuint64_t*, const cuuint64_t*, const cuuint32_t*,
                          const cuuint32_t*, CUtensorMapInterleave, CUtensorMapSwizzle, CUtensorMapL2promotion, CUtensorMapFloatOOBfill);

void make_map(EncFn enc, CUtensorMap* m, const void* ptr, uint64_t cols, uint64_t rows, uint32_t box_c, uint32_t box_r) {
  cuuint64_t gd[2] = {cols, rows}; cuuint64_t gs[1] = {cols * 2}; cuuint32_t bd[2] = {box_c, box_r}; cuuint32_t es[2] = {1, 1};
  enc(m, CU_TENSOR_MAP_DATA_TYPE_BFLOAT16, 2, const_cast<void*>(ptr), gd, gs, bd, es, CU_TENSOR_MAP_INTERLEAVE_NONE, CU_TENSOR_MAP_SWIZZLE_128B,
      CU_TENSOR_MAP_L2_PROMOTION_L2_256B, CU_TENSOR_MAP_FLOAT_OOB_FILL_NONE);
}

}

extern "C" void kernel_launch(void* const* d_in, const int* in_sizes, int n_in, void* d_out, int out_size) {
  (void)in_sizes; (void)n_in; (void)out_size;
  static EncFn enc = nullptr;
  if (!enc) {
    void* fn = nullptr; cudaDriverEntryPointQueryResult qr;
    cudaGetDriverEntryPoint("cuTensorMapEncodeTiled", &fn, cudaEnableDefault, &qr);
    enc = (EncFn)fn;
    cudaFuncSetAttribute(fused_kernel, cudaFuncAttributeMaxDynamicSharedMemorySize, SMEM_TOTAL);
  }
  Params p;
  make_map(enc, &p.mX, d_in[0], 512, 2048, 64, 128);
  make_map(enc, &p.mX64, d_in[0], 512, 2048, 64, 64);
  make_map(enc, &p.mSre, d_in[1], 2048, 2048, 64, 128);
  make_map(enc, &p.mSim, d_in[2], 2048, 2048, 64, 128);
  make_map(enc, &p.mHre, d_in[3], 512, 512, 64, 64);
  make_map(enc, &p.mHim, d_in[4], 512, 512, 64, 64);
  make_map(enc, &p.mWin, d_in[6], 1376, 512, 64, 32);
  make_map(enc, &p.mWsp, d_in[7], 2048, 2048, 64, 128);
  make_map(enc, &p.mWout, d_in[9], 512, 688, 64, 64);
  make_map(enc, &p.mOut, d_out, 512, 2048, 64, 64);
  p.x = (const __nv_bfloat16*)d_in[0]; p.hre = (const __nv_bfloat16*)d_in[3]; p.him = (const __nv_bfloat16*)d_in[4];
  p.win = (const __nv_bfloat16*)d_in[6]; p.bsp = (const __nv_bfloat16*)d_in[8]; p.wout = (const __nv_bfloat16*)d_in[9];
  {
    int order[64], n = 0;
    if (CMAP) {
      for (int pos = 0; pos < 8; pos++) for (int r = 0; r < 4; r++) order[n++] = 4 + r * 8 + pos;
      for (int pos = 0; pos < 7; pos++) for (int r = 0; r < 4; r++) order[n++] = 36 + r * 7 + pos;
      for (int i = 0; i < 4; i++) order[n++] = i;
      static const int sp[16] = {0, 1, 2, 3, 0, 1, 2, 3, 1, 0, 3, 2, 1, 0, 3, 2};
      int cnt[4] = {0, 0, 0, 0};
      for (int g = 0; g < 16; g++) for (int r = 0; r < 4; r++) { const int s = sp[g]; p.cmap[order[g * 4 + r]] = (uint8_t)((cnt[s]++ << 2) | s); }
    } else {
      for (int i = 0; i < 64; i++) p.cmap[i] = (uint8_t)i;
    }
  }
  cudaLaunchConfig_t cfg = {};
  cfg.gridDim = dim3(128); cfg.blockDim = dim3(384); cfg.dynamicSmemBytes = SMEM_TOTAL; cfg.stream = cudaStreamPerThread;
  cudaLaunchAttribute at[1];
  at[0].id = cudaLaunchAttributeClusterDimension; at[0].val.clusterDim.x = 2; at[0].val.clusterDim.y = 1; at[0].val.clusterDim.z = 1;
  cfg.attrs = at; cfg.numAttrs = 1;
  cudaLaunchKernelEx(&cfg, fused_kernel, p);
}
```

```cpp
#include <cuda_runtime.h>
#include <cuda_bf16.h>
#include <cuda.h>
#include <stdint.h>

namespace {

template<int TB> __device__ __forceinline__ void wgmma_n128(float* d, uint64_t da, uint64_t db, int sd) {
  asm volatile("{\n.reg .pred p;\n"
    "setp.ne.b32 p, %66, 0;\n"
    "wgmma.mma_async.sync.aligned.m64n128k16.f32.bf16.bf16 "
    "{%0,%1,%2,%3,%4,%5,%6,%7,%8,%9,%10,%11,%12,%13,%14,%15,%16,%17,%18,%19,%20,%21,%22,%23,%24,%25,%26,%27,%28,%29,%30,%31,%32,%33,%34,%35,%36,%37,%38,%39,%40,%41,%42,%43,%44,%45,%46,%47,%48,%49,%50,%51,%52,%53,%54,%55,%56,%57,%58,%59,%60,%61,%62,%63}, "
    "%64, %65, p, 1, 1, 0, %67;\n}\n"
    : "+f"(d[0]),"+f"(d[1]),"+f"(d[2]),"+f"(d[3]),"+f"(d[4]),"+f"(d[5]),"+f"(d[6]),"+f"(d[7]),"+f"(d[8]),"+f"(d[9]),"+f"(d[10]),"+f"(d[11]),"+f"(d[12]),"+f"(d[13]),"+f"(d[14]),"+f"(d[15]),"+f"(d[16]),"+f"(d[17]),"+f"(d[18]),"+f"(d[19]),"+f"(d[20]),"+f"(d[21]),"+f"(d[22]),"+f"(d[23]),"+f"(d[24]),"+f"(d[25]),"+f"(d[26]),"+f"(d[27]),"+f"(d[28]),"+f"(d[29]),"+f"(d[30]),"+f"(d[31]),"+f"(d[32]),"+f"(d[33]),"+f"(d[34]),"+f"(d[35]),"+f"(d[36]),"+f"(d[37]),"+f"(d[38]),"+f"(d[39]),"+f"(d[40]),"+f"(d[41]),"+f"(d[42]),"+f"(d[43]),"+f"(d[44]),"+f"(d[45]),"+f"(d[46]),"+f"(d[47]),"+f"(d[48]),"+f"(d[49]),"+f"(d[50]),"+f"(d[51]),"+f"(d[52]),"+f"(d[53]),"+f"(d[54]),"+f"(d[55]),"+f"(d[56]),"+f"(d[57]),"+f"(d[58]),"+f"(d[59]),"+f"(d[60]),"+f"(d[61]),"+f"(d[62]),"+f"(d[63])
    : "l"(da), "l"(db), "r"(sd), "n"(TB));
}
template<int TB> __device__ __forceinline__ void wgmma_n176(float* d, uint64_t da, uint64_t db, int sd) {
  asm volatile("{\n.reg .pred p;\n"
    "setp.ne.b32 p, %90, 0;\n"
    "wgmma.mma_async.sync.aligned.m64n176k16.f32.bf16.bf16 "
    "{%0,%1,%2,%3,%4,%5,%6,%7,%8,%9,%10,%11,%12,%13,%14,%15,%16,%17,%18,%19,%20,%21,%22,%23,%24,%25,%26,%27,%28,%29,%30,%31,%32,%33,%34,%35,%36,%37,%38,%39,%40,%41,%42,%43,%44,%45,%46,%47,%48,%49,%50,%51,%52,%53,%54,%55,%56,%57,%58,%59,%60,%61,%62,%63,%64,%65,%66,%67,%68,%69,%70,%71,%72,%73,%74,%75,%76,%77,%78,%79,%80,%81,%82,%83,%84,%85,%86,%87}, "
    "%88, %89, p, 1, 1, 0, %91;\n}\n"
    : "+f"(d[0]),"+f"(d[1]),"+f"(d[2]),"+f"(d[3]),"+f"(d[4]),"+f"(d[5]),"+f"(d[6]),"+f"(d[7]),"+f"(d[8]),"+f"(d[9]),"+f"(d[10]),"+f"(d[11]),"+f"(d[12]),"+f"(d[13]),"+f"(d[14]),"+f"(d[15]),"+f"(d[16]),"+f"(d[17]),"+f"(d[18]),"+f"(d[19]),"+f"(d[20]),"+f"(d[21]),"+f"(d[22]),"+f"(d[23]),"+f"(d[24]),"+f"(d[25]),"+f"(d[26]),"+f"(d[27]),"+f"(d[28]),"+f"(d[29]),"+f"(d[30]),"+f"(d[31]),"+f"(d[32]),"+f"(d[33]),"+f"(d[34]),"+f"(d[35]),"+f"(d[36]),"+f"(d[37]),"+f"(d[38]),"+f"(d[39]),"+f"(d[40]),"+f"(d[41]),"+f"(d[42]),"+f"(d[43]),"+f"(d[44]),"+f"(d[45]),"+f"(d[46]),"+f"(d[47]),"+f"(d[48]),"+f"(d[49]),"+f"(d[50]),"+f"(d[51]),"+f"(d[52]),"+f"(d[53]),"+f"(d[54]),"+f"(d[55]),"+f"(d[56]),"+f"(d[57]),"+f"(d[58]),"+f"(d[59]),"+f"(d[60]),"+f"(d[61]),"+f"(d[62]),"+f"(d[63]),"+f"(d[64]),"+f"(d[65]),"+f"(d[66]),"+f"(d[67]),"+f"(d[68]),"+f"(d[69]),"+f"(d[70]),"+f"(d[71]),"+f"(d[72]),"+f"(d[73]),"+f"(d[74]),"+f"(d[75]),"+f"(d[76]),"+f"(d[77]),"+f"(d[78]),"+f"(d[79]),"+f"(d[80]),"+f"(d[81]),"+f"(d[82]),"+f"(d[83]),"+f"(d[84]),"+f"(d[85]),"+f"(d[86]),"+f"(d[87])
    : "l"(da), "l"(db), "r"(sd), "n"(TB));
}
template<int TB> __device__ __forceinline__ void wgmma_n256(float* d, uint64_t da, uint64_t db, int sd) {
  asm volatile("{\n.reg .pred p;\n"
    "setp.ne.b32 p, %130, 0;\n"
    "wgmma.mma_async.sync.aligned.m64n256k16.f32.bf16.bf16 "
    "{%0,%1,%2,%3,%4,%5,%6,%7,%8,%9,%10,%11,%12,%13,%14,%15,%16,%17,%18,%19,%20,%21,%22,%23,%24,%25,%26,%27,%28,%29,%30,%31,%32,%33,%34,%35,%36,%37,%38,%39,%40,%41,%42,%43,%44,%45,%46,%47,%48,%49,%50,%51,%52,%53,%54,%55,%56,%57,%58,%59,%60,%61,%62,%63,%64,%65,%66,%67,%68,%69,%70,%71,%72,%73,%74,%75,%76,%77,%78,%79,%80,%81,%82,%83,%84,%85,%86,%87,%88,%89,%90,%91,%92,%93,%94,%95,%96,%97,%98,%99,%100,%101,%102,%103,%104,%105,%106,%107,%108,%109,%110,%111,%112,%113,%114,%115,%116,%117,%118,%119,%120,%121,%122,%123,%124,%125,%126,%127}, "
    "%128, %129, p, 1, 1, 0, %131;\n}\n"
    : "+f"(d[0]),"+f"(d[1]),"+f"(d[2]),"+f"(d[3]),"+f"(d[4]),"+f"(d[5]),"+f"(d[6]),"+f"(d[7]),"+f"(d[8]),"+f"(d[9]),"+f"(d[10]),"+f"(d[11]),"+f"(d[12]),"+f"(d[13]),"+f"(d[14]),"+f"(d[15]),"+f"(d[16]),"+f"(d[17]),"+f"(d[18]),"+f"(d[19]),"+f"(d[20]),"+f"(d[21]),"+f"(d[22]),"+f"(d[23]),"+f"(d[24]),"+f"(d[25]),"+f"(d[26]),"+f"(d[27]),"+f"(d[28]),"+f"(d[29]),"+f"(d[30]),"+f"(d[31]),"+f"(d[32]),"+f"(d[33]),"+f"(d[34]),"+f"(d[35]),"+f"(d[36]),"+f"(d[37]),"+f"(d[38]),"+f"(d[39]),"+f"(d[40]),"+f"(d[41]),"+f"(d[42]),"+f"(d[43]),"+f"(d[44]),"+f"(d[45]),"+f"(d[46]),"+f"(d[47]),"+f"(d[48]),"+f"(d[49]),"+f"(d[50]),"+f"(d[51]),"+f"(d[52]),"+f"(d[53]),"+f"(d[54]),"+f"(d[55]),"+f"(d[56]),"+f"(d[57]),"+f"(d[58]),"+f"(d[59]),"+f"(d[60]),"+f"(d[61]),"+f"(d[62]),"+f"(d[63]),"+f"(d[64]),"+f"(d[65]),"+f"(d[66]),"+f"(d[67]),"+f"(d[68]),"+f"(d[69]),"+f"(d[70]),"+f"(d[71]),"+f"(d[72]),"+f"(d[73]),"+f"(d[74]),"+f"(d[75]),"+f"(d[76]),"+f"(d[77]),"+f"(d[78]),"+f"(d[79]),"+f"(d[80]),"+f"(d[81]),"+f"(d[82]),"+f"(d[83]),"+f"(d[84]),"+f"(d[85]),"+f"(d[86]),"+f"(d[87]),"+f"(d[88]),"+f"(d[89]),"+f"(d[90]),"+f"(d[91]),"+f"(d[92]),"+f"(d[93]),"+f"(d[94]),"+f"(d[95]),"+f"(d[96]),"+f"(d[97]),"+f"(d[98]),"+f"(d[99]),"+f"(d[100]),"+f"(d[101]),"+f"(d[102]),"+f"(d[103]),"+f"(d[104]),"+f"(d[105]),"+f"(d[106]),"+f"(d[107]),"+f"(d[108]),"+f"(d[109]),"+f"(d[110]),"+f"(d[111]),"+f"(d[112]),"+f"(d[113]),"+f"(d[114]),"+f"(d[115]),"+f"(d[116]),"+f"(d[117]),"+f"(d[118]),"+f"(d[119]),"+f"(d[120]),"+f"(d[121]),"+f"(d[122]),"+f"(d[123]),"+f"(d[124]),"+f"(d[125]),"+f"(d[126]),"+f"(d[127])
    : "l"(da), "l"(db), "r"(sd), "n"(TB));
}
template<int TB> __device__ __forceinline__ void wgmma_rs_n128(float* d, uint4 a, uint64_t db, int sd) {
  asm volatile("{\n.reg .pred p;\n"
    "setp.ne.b32 p, %69, 0;\n"
    "wgmma.mma_async.sync.aligned.m64n128k16.f32.bf16.bf16 "
    "{%0,%1,%2,%3,%4,%5,%6,%7,%8,%9,%10,%11,%12,%13,%14,%15,%16,%17,%18,%19,%20,%21,%22,%23,%24,%25,%26,%27,%28,%29,%30,%31,%32,%33,%34,%35,%36,%37,%38,%39,%40,%41,%42,%43,%44,%45,%46,%47,%48,%49,%50,%51,%52,%53,%54,%55,%56,%57,%58,%59,%60,%61,%62,%63}, "
    "{%64,%65,%66,%67}, %68, p, 1, 1, %70;\n}\n"
    : "+f"(d[0]),"+f"(d[1]),"+f"(d[2]),"+f"(d[3]),"+f"(d[4]),"+f"(d[5]),"+f"(d[6]),"+f"(d[7]),"+f"(d[8]),"+f"(d[9]),"+f"(d[10]),"+f"(d[11]),"+f"(d[12]),"+f"(d[13]),"+f"(d[14]),"+f"(d[15]),"+f"(d[16]),"+f"(d[17]),"+f"(d[18]),"+f"(d[19]),"+f"(d[20]),"+f"(d[21]),"+f"(d[22]),"+f"(d[23]),"+f"(d[24]),"+f"(d[25]),"+f"(d[26]),"+f"(d[27]),"+f"(d[28]),"+f"(d[29]),"+f"(d[30]),"+f"(d[31]),"+f"(d[32]),"+f"(d[33]),"+f"(d[34]),"+f"(d[35]),"+f"(d[36]),"+f"(d[37]),"+f"(d[38]),"+f"(d[39]),"+f"(d[40]),"+f"(d[41]),"+f"(d[42]),"+f"(d[43]),"+f"(d[44]),"+f"(d[45]),"+f"(d[46]),"+f"(d[47]),"+f"(d[48]),"+f"(d[49]),"+f"(d[50]),"+f"(d[51]),"+f"(d[52]),"+f"(d[53]),"+f"(d[54]),"+f"(d[55]),"+f"(d[56]),"+f"(d[57]),"+f"(d[58]),"+f"(d[59]),"+f"(d[60]),"+f"(d[61]),"+f"(d[62]),"+f"(d[63])
    : "r"(a.x), "r"(a.y), "r"(a.z), "r"(a.w), "l"(db), "r"(sd), "n"(TB));
}
template<int TB> __device__ __forceinline__ void wgmma_rs_n176(float* d, uint4 a, uint64_t db, int sd) {
  asm volatile("{\n.reg .pred p;\n"
    "setp.ne.b32 p, %93, 0;\n"
    "wgmma.mma_async.sync.aligned.m64n176k16.f32.bf16.bf16 "
    "{%0,%1,%2,%3,%4,%5,%6,%7,%8,%9,%10,%11,%12,%13,%14,%15,%16,%17,%18,%19,%20,%21,%22,%23,%24,%25,%26,%27,%28,%29,%30,%31,%32,%33,%34,%35,%36,%37,%38,%39,%40,%41,%42,%43,%44,%45,%46,%47,%48,%49,%50,%51,%52,%53,%54,%55,%56,%57,%58,%59,%60,%61,%62,%63,%64,%65,%66,%67,%68,%69,%70,%71,%72,%73,%74,%75,%76,%77,%78,%79,%80,%81,%82,%83,%84,%85,%86,%87}, "
    "{%88,%89,%90,%91}, %92, p, 1, 1, %94;\n}\n"
    : "+f"(d[0]),"+f"(d[1]),"+f"(d[2]),"+f"(d[3]),"+f"(d[4]),"+f"(d[5]),"+f"(d[6]),"+f"(d[7]),"+f"(d[8]),"+f"(d[9]),"+f"(d[10]),"+f"(d[11]),"+f"(d[12]),"+f"(d[13]),"+f"(d[14]),"+f"(d[15]),"+f"(d[16]),"+f"(d[17]),"+f"(d[18]),"+f"(d[19]),"+f"(d[20]),"+f"(d[21]),"+f"(d[22]),"+f"(d[23]),"+f"(d[24]),"+f"(d[25]),"+f"(d[26]),"+f"(d[27]),"+f"(d[28]),"+f"(d[29]),"+f"(d[30]),"+f"(d[31]),"+f"(d[32]),"+f"(d[33]),"+f"(d[34]),"+f"(d[35]),"+f"(d[36]),"+f"(d[37]),"+f"(d[38]),"+f"(d[39]),"+f"(d[40]),"+f"(d[41]),"+f"(d[42]),"+f"(d[43]),"+f"(d[44]),"+f"(d[45]),"+f"(d[46]),"+f"(d[47]),"+f"(d[48]),"+f"(d[49]),"+f"(d[50]),"+f"(d[51]),"+f"(d[52]),"+f"(d[53]),"+f"(d[54]),"+f"(d[55]),"+f"(d[56]),"+f"(d[57]),"+f"(d[58]),"+f"(d[59]),"+f"(d[60]),"+f"(d[61]),"+f"(d[62]),"+f"(d[63]),"+f"(d[64]),"+f"(d[65]),"+f"(d[66]),"+f"(d[67]),"+f"(d[68]),"+f"(d[69]),"+f"(d[70]),"+f"(d[71]),"+f"(d[72]),"+f"(d[73]),"+f"(d[74]),"+f"(d[75]),"+f"(d[76]),"+f"(d[77]),"+f"(d[78]),"+f"(d[79]),"+f"(d[80]),"+f"(d[81]),"+f"(d[82]),"+f"(d[83]),"+f"(d[84]),"+f"(d[85]),"+f"(d[86]),"+f"(d[87])
    : "r"(a.x), "r"(a.y), "r"(a.z), "r"(a.w), "l"(db), "r"(sd), "n"(TB));
}

__device__ __align__(1024) uint8_t g_ab[2 * 32 * 4 * 16384];
__device__ __align__(1024) uint8_t g_z2[32 * 4 * 24576];
__device__ __align__(1024) uint4 g_op[64 * 2 * 8 * 128];
__device__ __align__(1024) uint4 g_yp[64 * 2 * 8 * 256];
__device__ __align__(128) uint32_t g_rs[2048];
__device__ __align__(128) uint32_t g_hs[1024];
__device__ __align__(128) uint32_t g_ws[4 * 1408];
__device__ __align__(128) uint2 g_ln2[2048 * 4];
__device__ __align__(128) uint32_t g_fab[2 * 32 * 4 * 32];
__device__ __align__(128) uint32_t g_fz2[4 * 32 * 32];
__device__ __align__(128) uint32_t g_epoch[132];
#define PROF_T2(i) do {} while (0)
#define PROF_W0() do {} while (0)
#define PROF_W1(a) do {} while (0)
#define PROF_V(i, v) do {} while (0)
#define PROF_T(i) do {} while (0)
#define PROF_DECL(v) do {} while (0)

struct alignas(64) Params {
  CUtensorMap mX, mX64, mHre, mHim, mWin, mSre, mSim, mWsp, mWout, mOut;
  const __nv_bfloat16 *x, *hre, *him, *win, *bsp, *wout;
  uint8_t cmap[66];
};

constexpr uint32_t SMEM_TOTAL = 232448;
constexpr uint32_t A_STG = 49152, A_STAGING = 196608;
constexpr uint32_t B_STG = 40960, B_S0 = 65536, B_WO = 45056, B_W1 = 131072;
constexpr uint32_t MISC = 229376;
constexpr uint32_t BAR_FULL = MISC, BAR_EMPTY = MISC + 40, BAR_XFULL = MISC + 80, BAR_F1 = MISC + 144, BAR_E1 = MISC + 176,
                   BAR_STQ = MISC + 208, BAR_STGFREE = MISC + 240, BAR_P1 = MISC + 256, BAR_EXT = MISC + 264, BAR_GATE = MISC + 272,
                   BAR_PUB = MISC + 280, BAR_UB = MISC + 288;
constexpr uint32_t OFF_CLAIM = MISC + 328, OFF_RS = MISC + 336, A_EXT = MISC + 1024, B_RED = MISC + 1024;
#define PF_DIST 4
#define CMAP 6
#define PRO_T 3
#define ROT_MASK 12
#define REG_LO "40"
#define REG_HI "232"
#define PREP_T 1
#define PREP_WA 2
#define PREP_WB 1
#define PREP_EARLY 1
#define GATHER_NS 100
#define IDLE_NS 100
#define OWN256 8
#define PF_A 0
#define LATE_N 0
#define POLL_NS 0
#define A1_EARLY 1
#define PIECE 4096
#define PIECE_NS 500
#define SKEW_B 2
#define SKEW_A 4
#define LATE_PF 1
#define TICKA 0
#define TICKB 0
#define PRB 0
#define EVF 1
#define PROMO CU_TENSOR_MAP_L2_PROMOTION_L2_128B
#define EVW 0
#define EVO 0
#define EVY 0
#define EVP 0
#define FIN_PIPE 1
#define PF0 0
#define PROMO1 PROMO
#define PREP_V 4
#define GATHER_B 0
#define PREP_SPLIT 1
#define STAG 1
#define STAG0 5
#define STAG1 7
#define PREFLAG 0
#define STG_B 16384
#define PRIO_A 0
#define XFIRST 0
#define RS_NS 100
#define HOLD_S 1
#define HOLD_W 0
#define PF_S 1
#define PF_LAST 26
#define OWNB 1
#define HGELU 0
#define Z_OUT 11
#define Z_IN 26
#define PEEL 0
#define PEEL_K0 23
#define PEEL_K1 35
#define EPOLL 0
#define FSTR 1
#define RLXPOLL 0
#define A1_N 5
#define CFIRST 0
#define ENDBAR 1
#define OWNA 1
#define EARLY_ST 0
#define HPREP 1
#define WARM 0
#define LATE_CW 0
#define PRO_T0 PRO_T
#define MIDREL 0
#define SMIDMAP 0
#define ARITH 0
#define PFL 0
#define PFX 0
#define NS 2
#define N0 1
#define GATE_A 3
#define GATE_B 3
constexpr int SPIN_LIMIT = 1 << 22;

__device__ __forceinline__ void spin_guard(int n) {
  asm volatile("{\n.reg .pred q;\n.reg .u64 z;\nmov.u64 z, 0;\nsetp.gt.s32 q, %0, %1;\n@q st.global.u32 [z], %0;\n}\n" ::"r"(n), "n"(SPIN_LIMIT) : "memory");
}
template <int Q> __device__ __forceinline__ void tick_align() {
  if (Q) {
    uint32_t t0, t;
    asm volatile("mov.u32 %0, %%globaltimer_lo;" : "=r"(t0));
    do { asm volatile("mov.u32 %0, %%globaltimer_lo;" : "=r"(t)); } while (((t ^ t0) & ~(uint32_t)(Q - 1)) == 0);
  }
}
__device__ __forceinline__ bool elect_one() {
  uint32_t ok;
  asm volatile("{\n.reg .pred p;\nelect.sync _|p, 0xffffffff;\nselp.u32 %0, 1, 0, p;\n}\n" : "=r"(ok));
  return ok;
}
__device__ __forceinline__ void mbar_init(uint32_t bar, uint32_t cnt) { asm volatile("mbarrier.init.shared::cta.b64 [%0], %1;" ::"r"(bar), "r"(cnt) : "memory"); }
__device__ __forceinline__ void mbar_expect_tx(uint32_t bar, uint32_t tx) { asm volatile("mbarrier.arrive.expect_tx.shared::cta.b64 _, [%0], %1;" ::"r"(bar), "r"(tx) : "memory"); }
__device__ __forceinline__ void mbar_arrive(uint32_t bar) { asm volatile("mbarrier.arrive.shared::cta.b64 _, [%0];" ::"r"(bar) : "memory"); }
__device__ __forceinline__ void mbar_arrive_n(uint32_t bar, uint32_t n) { asm volatile("mbarrier.arrive.shared::cta.b64 _, [%0], %1;" ::"r"(bar), "r"(n) : "memory"); }
__device__ __forceinline__ bool mbar_try(uint32_t bar, uint32_t par) {
  uint32_t ok;
  asm volatile("{\n.reg .pred p;\nmbarrier.try_wait.parity.shared::cta.b64 p, [%1], %2;\nselp.u32 %0, 1, 0, p;\n}\n" : "=r"(ok) : "r"(bar), "r"(par) : "memory");
  return ok;
}
__device__ __forceinline__ bool mbar_test(uint32_t bar, uint32_t par) {
  uint32_t ok;
  asm volatile("{\n.reg .pred p;\nmbarrier.test_wait.parity.shared::cta.b64 p, [%1], %2;\nselp.u32 %0, 1, 0, p;\n}\n" : "=r"(ok) : "r"(bar), "r"(par) : "memory");
  return __shfl_sync(0xffffffffu, ok, 0);
}
__device__ __forceinline__ void mbar_wait(uint32_t bar, uint32_t par) {
  int n = 0;
  while (!mbar_try(bar, par)) { spin_guard(++n); }
}
__device__ __forceinline__ void mbar_wait_cluster(uint32_t bar, uint32_t par) {
  int n = 0;
  while (true) {
    uint32_t ok;
    asm volatile("{\n.reg .pred p;\nmbarrier.try_wait.parity.acquire.cluster.shared::cta.b64 p, [%1], %2;\nselp.u32 %0, 1, 0, p;\n}\n" : "=r"(ok) : "r"(bar), "r"(par) : "memory");
    if (ok) break;
    spin_guard(++n);
  }
}
__device__ __forceinline__ void mbar_wait_idle(uint32_t bar, uint32_t par) {
  int n = 0;
  while (!mbar_try(bar, par)) { spin_guard(++n); __nanosleep(IDLE_NS); }
}
__device__ __forceinline__ void tma_2d(uint32_t dst, const CUtensorMap* m, int c0, int c1, uint32_t bar) {
  asm volatile("cp.async.bulk.tensor.2d.shared::cluster.global.mbarrier::complete_tx::bytes [%0], [%1, {%3, %4}], [%2];"
               ::"r"(dst), "l"(m), "r"(bar), "r"(c0), "r"(c1) : "memory");
}
__device__ __forceinline__ void tma_2d_mc(uint32_t dst, const CUtensorMap* m, int c0, int c1, uint32_t bar) {
  asm volatile("cp.async.bulk.tensor.2d.shared::cluster.global.mbarrier::complete_tx::bytes.multicast::cluster [%0], [%1, {%3, %4}], [%2], %5;"
               ::"r"(dst), "l"(m), "r"(bar), "r"(c0), "r"(c1), "h"((uint16_t)3) : "memory");
}
__device__ __forceinline__ void tma_2d_mc_stream(uint32_t dst, const CUtensorMap* m, int c0, int c1, uint32_t bar) {
  asm volatile("{\n.reg .b64 pol;\ncreatepolicy.fractional.L2::evict_first.b64 pol, 1.0;\n"
               "cp.async.bulk.tensor.2d.shared::cluster.global.mbarrier::complete_tx::bytes.multicast::cluster.L2::cache_hint [%0], [%1, {%3, %4}], [%2], %5, pol;\n}\n"
               ::"r"(dst), "l"(m), "r"(bar), "r"(c0), "r"(c1), "h"((uint16_t)3) : "memory");
}
__device__ __forceinline__ void release(uint32_t bar, int lane, uint32_t n) {
  if (lane < 2)
    asm volatile("{\n.reg .b32 ra;\nmapa.shared::cluster.u32 ra, %0, %1;\nmbarrier.arrive.shared::cluster.b64 _, [ra], %2;\n}\n" ::"r"(bar), "r"(lane), "r"(n) : "memory");
}
__device__ __forceinline__ uint32_t map_peer(uint32_t a, uint32_t cta) { uint32_t r; asm("mapa.shared::cluster.u32 %0, %1, %2;" : "=r"(r) : "r"(a), "r"(cta)); return r; }
__device__ __forceinline__ void st_async4(uint32_t dst, uint4 v, uint32_t bar) {
  asm volatile("st.async.weak.shared::cluster.mbarrier::complete_tx::bytes.v4.b32 [%0], {%1,%2,%3,%4}, [%5];" ::"r"(dst), "r"(v.x), "r"(v.y), "r"(v.z), "r"(v.w), "r"(bar) : "memory");
}
__device__ __forceinline__ void cluster_arrive() { asm volatile("barrier.cluster.arrive.relaxed.aligned;" ::: "memory"); }
__device__ __forceinline__ void cluster_wait() { asm volatile("barrier.cluster.wait.acquire.aligned;" ::: "memory"); }
__device__ __forceinline__ void tma_store_2d(const CUtensorMap* m, int c0, int c1, uint32_t src) {
  asm volatile("cp.async.bulk.tensor.2d.global.shared::cta.bulk_group [%0, {%2, %3}], [%1];" ::"l"(m), "r"(src), "r"(c0), "r"(c1) : "memory");
}
__device__ __forceinline__ void tma_prefetch_2d(const CUtensorMap* m, int c0, int c1) {
  asm volatile("cp.async.bulk.prefetch.tensor.2d.L2.global [%0, {%1, %2}];" ::"l"(m), "r"(c0), "r"(c1) : "memory");
}
__device__ __forceinline__ void bulk_prefetch(const void* src, uint32_t bytes) { asm volatile("cp.async.bulk.prefetch.L2.global [%0], %1;" ::"l"(src), "r"(bytes) : "memory"); }
__device__ __forceinline__ void prefetch_map(const CUtensorMap* m) { asm volatile("prefetch.tensormap [%0];" ::"l"(m) : "memory"); }
__device__ __forceinline__ void bulk_g2s(uint32_t dst, const void* src, uint32_t bytes, uint32_t bar) {
  asm volatile("cp.async.bulk.shared::cluster.global.mbarrier::complete_tx::bytes [%0], [%1], %2, [%3];" ::"r"(dst), "l"(src), "r"(bytes), "r"(bar) : "memory");
}
__device__ __forceinline__ void bulk_g2s_stream(uint32_t dst, const void* src, uint32_t bytes, uint32_t bar) {
  bulk_g2s(dst, src, bytes, bar);
}
__device__ __forceinline__ void bulk_s2g(void* dst, uint32_t src, uint32_t bytes) {
  asm volatile("cp.async.bulk.global.shared::cta.bulk_group [%0], [%1], %2;" ::"l"(dst), "r"(src), "r"(bytes) : "memory");
}
__device__ __forceinline__ void bulk_commit() { asm volatile("cp.async.bulk.commit_group;" ::: "memory"); }
__device__ __forceinline__ void bulk_wait_read() { asm volatile("cp.async.bulk.wait_group.read 0;" ::: "memory"); }
__device__ __forceinline__ void bulk_wait_all() { asm volatile("cp.async.bulk.wait_group 0;" ::: "memory"); }
__device__ __forceinline__ void fence_async_smem() { asm volatile("fence.proxy.async.shared::cta;" ::: "memory"); }
__device__ __forceinline__ void fence_async_global() { asm volatile("fence.proxy.async.global;" ::: "memory"); }
__device__ __forceinline__ void wg_fence() { asm volatile("wgmma.fence.sync.aligned;" ::: "memory"); }
__device__ __forceinline__ void wg_commit() { asm volatile("wgmma.commit_group.sync.aligned;" ::: "memory"); }
template <int N> __device__ __forceinline__ void wg_wait() { asm volatile("wgmma.wait_group.sync.aligned %0;" ::"n"(N) : "memory"); }
__device__ __forceinline__ void bar_sync(int id, int n) { asm volatile("bar.sync %0, %1;" ::"r"(id), "r"(n) : "memory"); }
__device__ __forceinline__ void bar_arrive(int id, int n) { asm volatile("bar.arrive %0, %1;" ::"r"(id), "r"(n) : "memory"); }
__device__ __forceinline__ uint64_t desc_k(uint32_t addr) {
  return (uint64_t)((addr & 0x3FFFF) >> 4) | (1ull << 16) | (64ull << 32) | (1ull << 62);
}
__device__ __forceinline__ uint64_t desc_n(uint32_t addr) {
  return (uint64_t)((addr & 0x3FFFF) >> 4) | (512ull << 16) | (64ull << 32) | (1ull << 62);
}
__device__ __forceinline__ uint64_t desc_ext(uint32_t addr) {
  return (uint64_t)((addr & 0x3FFFF) >> 4) | (8ull << 32);
}
__device__ __forceinline__ void stsm4(uint32_t a, uint32_t r0, uint32_t r1, uint32_t r2, uint32_t r3) {
  asm volatile("stmatrix.sync.aligned.m8n8.x4.shared.b16 [%0], {%1,%2,%3,%4};" ::"r"(a), "r"(r0), "r"(r1), "r"(r2), "r"(r3) : "memory");
}
__device__ __forceinline__ void stsm4t(uint32_t a, uint32_t r0, uint32_t r1, uint32_t r2, uint32_t r3) {
  asm volatile("stmatrix.sync.aligned.m8n8.x4.trans.shared.b16 [%0], {%1,%2,%3,%4};" ::"r"(a), "r"(r0), "r"(r1), "r"(r2), "r"(r3) : "memory");
}
__device__ __forceinline__ void ldsm4(uint32_t a, uint32_t& r0, uint32_t& r1, uint32_t& r2, uint32_t& r3) {
  asm volatile("ldmatrix.sync.aligned.m8n8.x4.shared.b16 {%0,%1,%2,%3}, [%4];" : "=r"(r0), "=r"(r1), "=r"(r2), "=r"(r3) : "r"(a) : "memory");
}
__device__ __forceinline__ uint32_t pack2(float lo, float hi) {
  uint32_t r; asm("cvt.rn.bf16x2.f32 %0, %1, %2;" : "=r"(r) : "f"(hi), "f"(lo)); return r;
}
__device__ __forceinline__ float bf_lo(uint32_t v) { return __uint_as_float(v << 16); }
__device__ __forceinline__ float bf_hi(uint32_t v) { return __uint_as_float(v & 0xFFFF0000u); }
__device__ __forceinline__ float round_bf(float v) { return bf_lo(pack2(v, 0.f)); }
__device__ __forceinline__ float2 lds64(uint32_t a) { float2 v; asm volatile("ld.shared.v2.f32 {%0,%1}, [%2];" : "=f"(v.x), "=f"(v.y) : "r"(a) : "memory"); return v; }
__device__ __forceinline__ float lds32(uint32_t a) { float v; asm volatile("ld.shared.f32 %0, [%1];" : "=f"(v) : "r"(a) : "memory"); return v; }
__device__ __forceinline__ uint32_t lds32u(uint32_t a) { uint32_t v; asm volatile("ld.shared.b32 %0, [%1];" : "=r"(v) : "r"(a) : "memory"); return v; }
__device__ __forceinline__ void sts32(uint32_t a, float v) { asm volatile("st.shared.f32 [%0], %1;" ::"r"(a), "f"(v) : "memory"); }
__device__ __forceinline__ void sts64u(uint32_t a, uint32_t x, uint32_t y) { asm volatile("st.shared.v2.b32 [%0], {%1,%2};" ::"r"(a), "r"(x), "r"(y) : "memory"); }
__device__ __forceinline__ uint4 lds128(uint32_t a) { uint4 v; asm volatile("ld.shared.v4.b32 {%0,%1,%2,%3}, [%4];" : "=r"(v.x), "=r"(v.y), "=r"(v.z), "=r"(v.w) : "r"(a) : "memory"); return v; }
__device__ __forceinline__ void sts128(uint32_t a, uint4 v) { asm volatile("st.shared.v4.b32 [%0], {%1,%2,%3,%4};" ::"r"(a), "r"(v.x), "r"(v.y), "r"(v.z), "r"(v.w) : "memory"); }
__device__ __forceinline__ uint32_t ld_rlx(const uint32_t* p) { uint32_t v; asm volatile("ld.relaxed.gpu.global.b32 %0, [%1];" : "=r"(v) : "l"(p) : "memory"); return v; }
__device__ __forceinline__ uint32_t ld_acq(const uint32_t* p) { uint32_t v; asm volatile("ld.acquire.gpu.global.b32 %0, [%1];" : "=r"(v) : "l"(p) : "memory"); return v; }
__device__ __forceinline__ uint2 ld_rlx2(const uint2* p) { uint2 v; asm volatile("ld.relaxed.gpu.global.v2.b32 {%0,%1}, [%2];" : "=r"(v.x), "=r"(v.y) : "l"(p) : "memory"); return v; }
__device__ __forceinline__ uint4 ld_rlx4(const uint4* p) { uint4 v; asm volatile("ld.relaxed.gpu.global.v4.b32 {%0,%1,%2,%3}, [%4];" : "=r"(v.x), "=r"(v.y), "=r"(v.z), "=r"(v.w) : "l"(p) : "memory"); return v; }
__device__ __forceinline__ void st_rlx(uint32_t* p, uint32_t v) { asm volatile("st.relaxed.gpu.global.b32 [%0], %1;" ::"l"(p), "r"(v) : "memory"); }
__device__ __forceinline__ void st_rel(uint32_t* p, uint32_t v) { asm volatile("st.release.gpu.global.b32 [%0], %1;" ::"l"(p), "r"(v) : "memory"); }
__device__ __forceinline__ void st_rlx2(uint2* p, uint32_t x, uint32_t y) { asm volatile("st.relaxed.gpu.global.v2.b32 [%0], {%1,%2};" ::"l"(p), "r"(x), "r"(y) : "memory"); }
__device__ __forceinline__ void st_rlx4(uint4* p, uint32_t x, uint32_t y, uint32_t z, uint32_t w) { asm volatile("st.relaxed.gpu.global.v4.b32 [%0], {%1,%2,%3,%4};" ::"l"(p), "r"(x), "r"(y), "r"(z), "r"(w) : "memory"); }
__device__ __forceinline__ uint4 ldg128(const void* p) { uint4 v; asm volatile("ld.global.nc.v4.b32 {%0,%1,%2,%3}, [%4];" : "=r"(v.x), "=r"(v.y), "=r"(v.z), "=r"(v.w) : "l"(p)); return v; }
__device__ __forceinline__ uint32_t tagf(float v, uint32_t par) { return (__float_as_uint(v) & ~1u) | par; }
__device__ __forceinline__ float tanh_fast(float v) { float r; asm("tanh.approx.f32 %0, %1;" : "=f"(r) : "f"(v)); return r; }
__device__ __forceinline__ float gelu_h(float h) {
  const float u = h * fmaf(h * h, 8.f * 0.7978845608f * 0.044715f, 2.f * 0.7978845608f);
  return fmaf(h, tanh_fast(u), h);
}
__device__ __forceinline__ float silu_f(float v) { const float h = 0.5f * v; return fmaf(h, tanh_fast(h), h); }
__device__ __forceinline__ uint32_t bmul2(uint32_t a, uint32_t b) { uint32_t r; asm("mul.rn.bf16x2 %0, %1, %2;" : "=r"(r) : "r"(a), "r"(b)); return r; }
__device__ __forceinline__ uint32_t badd2(uint32_t a, uint32_t b) { uint32_t r; asm("add.rn.bf16x2 %0, %1, %2;" : "=r"(r) : "r"(a), "r"(b)); return r; }
__device__ __forceinline__ uint32_t bfma2(uint32_t a, uint32_t b, uint32_t c) { uint32_t r; asm("fma.rn.bf16x2 %0, %1, %2, %3;" : "=r"(r) : "r"(a), "r"(b), "r"(c)); return r; }
__device__ __forceinline__ float sum8(uint4 v) {
  return ((bf_lo(v.x) + bf_hi(v.x)) + (bf_lo(v.y) + bf_hi(v.y))) + ((bf_lo(v.z) + bf_hi(v.z)) + (bf_lo(v.w) + bf_hi(v.w)));
}
__device__ __forceinline__ void acc_sq(uint4 v, float& s, float& q) {
  const float a0 = bf_lo(v.x), a1 = bf_hi(v.x), a2 = bf_lo(v.y), a3 = bf_hi(v.y), a4 = bf_lo(v.z), a5 = bf_hi(v.z), a6 = bf_lo(v.w), a7 = bf_hi(v.w);
  s += ((a0 + a1) + (a2 + a3)) + ((a4 + a5) + (a6 + a7));
  q += fmaf(a0, a0, fmaf(a1, a1, fmaf(a2, a2, a3 * a3))) + fmaf(a4, a4, fmaf(a5, a5, fmaf(a6, a6, a7 * a7)));
}
template <int N> __device__ __forceinline__ void zero_acc(float* a) {
#pragma unroll
  for (int i = 0; i < N; i++) a[i] = 0.f;
}
__device__ __forceinline__ float rcp_fast(float v) { float r; asm("rcp.approx.ftz.f32 %0, %1;" : "=f"(r) : "f"(v)); return r; }
__device__ __forceinline__ float std_ref(float var) {
  float s;
  asm("sqrt.approx.ftz.f32 %0, %1;" : "=f"(s) : "f"(round_bf(round_bf(fmaxf(var, 0.f)) + 1e-5f)));
  return s;
}
__device__ __forceinline__ float rstd_ref(float var) { return rcp_fast(round_bf(std_ref(var))); }
__device__ __forceinline__ float rs_rstd(uint32_t w) { return rcp_fast(__uint_as_float((w & 0x7FFFu) << 16)); }
__device__ __forceinline__ uint4 ext_frag(uint32_t r0, uint32_t r1, int i4, int w) {
  const uint32_t n0 = (r0 >> 16) ^ 0x8000u, n1 = (r1 >> 16) ^ 0x8000u;
  const uint32_t mul = i4 == 2 * w ? 0x10001u : i4 == 2 * w + 1 ? 1u : 0u;
  return make_uint4(n0 * mul, n1 * mul, 0, 0);
}

__device__ __forceinline__ uint32_t load_epoch() { return ld_rlx(&g_epoch[blockIdx.x]) + 1; }
__device__ __forceinline__ void wait_flags(uint32_t& mask, uint32_t need, const uint32_t* f, uint32_t epoch) {
  if ((mask & need) == need) return;
  int n = 0;
  while (true) {
    mask = __ballot_sync(0xffffffffu, ld_acq(f) == epoch);
    if ((mask & need) == need) break;
    spin_guard(++n);
  }
  __syncwarp();
  fence_async_global();
}
__device__ __forceinline__ void publish(uint32_t* f, uint32_t epoch) { st_rel(f, epoch); }

__device__ __forceinline__ void colsum_add(float* cc, uint4 v) {
  cc[0] += bf_lo(v.x); cc[1] += bf_hi(v.x); cc[2] += bf_lo(v.y); cc[3] += bf_hi(v.y);
  cc[4] += bf_lo(v.z); cc[5] += bf_hi(v.z); cc[6] += bf_lo(v.w); cc[7] += bf_hi(v.w);
}
__device__ __forceinline__ void colsum_quad(float* cc, int i4) {
  const bool u1 = i4 & 1, u2 = i4 & 2;
#pragma unroll
  for (int k = 0; k < 4; k++) cc[k] = (u2 ? cc[k + 4] : cc[k]) + __shfl_xor_sync(0xffffffffu, u2 ? cc[k] : cc[k + 4], 2);
#pragma unroll
  for (int k = 0; k < 2; k++) cc[k] = (u1 ? cc[k + 2] : cc[k]) + __shfl_xor_sync(0xffffffffu, u1 ? cc[k] : cc[k + 2], 1);
}
__device__ __forceinline__ void role_C(const Params& p, uint32_t sb) {
  const int wp = __shfl_sync(0xffffffffu, (int)(threadIdx.x >> 5), 0), lane = threadIdx.x & 31, u = 64 + (blockIdx.x & 3) * 6 + (wp >> 1), i4 = lane & 3;
  const uint32_t bar = sb + MISC + wp * 8, wb = sb + wp * 8192;
  if (elect_one()) {
    mbar_init(bar, 1);
    fence_async_smem();
    mbar_expect_tx(bar, 8192);
    tma_2d(wb, &p.mWin, (u % 22) * 64, (u / 22) * 128 + (wp & 1) * 64, bar);
  }
  const uint32_t par = load_epoch() & 1u;
  __syncwarp();
  mbar_wait(bar, 0);
  float cc[8] = {0.f, 0.f, 0.f, 0.f, 0.f, 0.f, 0.f, 0.f};
#pragma unroll 4
  for (int t = 0; t < 16; t++) { const int row = t * 4 + i4; colsum_add(cc, lds128(wb + row * 128 + (((lane >> 2) ^ (row & 7)) << 4))); }
  colsum_quad(cc, i4);
  const uint32_t red = sb + 98304 + (wp >> 1) * 256 + lane * 8;
  if (wp & 1) sts64u(red, __float_as_uint(cc[0]), __float_as_uint(cc[1]));
  __syncthreads();
  if (!(wp & 1)) {
    const float2 o = lds64(red);
    st_rlx2((uint2*)&g_ws[(u / 22) * 1408 + (u % 22) * 64 + lane * 2], tagf(cc[0] + o.x, par), tagf(cc[1] + o.y, par));
  }
  if (threadIdx.x == 0) asm volatile("red.relaxed.gpu.global.add.u32 [%0], 1;" ::"l"(&g_epoch[blockIdx.x]) : "memory");
}

template <int NPART> __device__ __forceinline__ void gather(uint32_t sb, uint32_t ext, int ht, uint32_t par, int rb, const uint32_t* cs, int c0a, int c0b, int ncol) {
  const int e = ht * 4, set = e >= ncol, col = set ? e - ncol : e;
  const bool on = e < 2 * ncol;
  const uint4* cp = (const uint4*)&cs[on ? (set ? c0b : c0a) + col : c0a];
  const uint4* rp = (const uint4*)&g_rs[rb * 128 + (ht & 31) * 4];
  if (RS_NS && ht >= 32) __nanosleep((ht >> 5) * RS_NS);
  if (ht == 0) PROF_T(19);
  uint4 v[NPART], rs = ld_rlx4(rp);
  int n = 0;
  while (true) {
#pragma unroll
    for (int k = 0; k < NPART; k++) v[k] = ld_rlx4(cp + k * 352);
    uint32_t bad = 0;
#pragma unroll
    for (int k = 0; k < NPART; k++) bad |= (v[k].x ^ par) | (v[k].y ^ par) | (v[k].z ^ par) | (v[k].w ^ par);
    if (!(bad & 1u)) break;
    spin_guard(++n);
  }
  if (ht == 0) PROF_V(15, n * 1000);
  if (on) {
    float s[4] = {__uint_as_float(v[0].x), __uint_as_float(v[0].y), __uint_as_float(v[0].z), __uint_as_float(v[0].w)};
#pragma unroll
    for (int k = 1; k < NPART; k++) { s[0] += __uint_as_float(v[k].x); s[1] += __uint_as_float(v[k].y); s[2] += __uint_as_float(v[k].z); s[3] += __uint_as_float(v[k].w); }
#pragma unroll
    for (int k = 0; k < 4; k++) {
      const float hi = round_bf(s[k]), mid = round_bf(s[k] - hi);
      sts64u(ext + (col + k) * 16 + set * 8, pack2(hi, mid), pack2(s[k] - hi - mid, 0.f));
    }
  }
  fence_async_smem();
  mbar_arrive(sb + BAR_EXT);
  __syncwarp();
  if (ht == 0) PROF_T(6);
  while (!__any_sync(0xffffffffu, lds32u(sb + OFF_CLAIM) != 0)) {
    if (__all_sync(0xffffffffu, ((((rs.x ^ (par << 15)) | (rs.y ^ (par << 15)) | (rs.z ^ (par << 15)) | (rs.w ^ (par << 15))) >> 15) & 1u) == 0)) {
      uint32_t old = 1;
      if ((ht & 31) == 0) asm volatile("atom.shared.exch.b32 %0, [%1], 1;" : "=r"(old) : "r"(sb + OFF_CLAIM) : "memory");
      if (__shfl_sync(0xffffffffu, old, 0) == 0) {
        sts128(sb + OFF_RS + (ht & 31) * 16, rs);
        mbar_arrive(sb + BAR_EXT);
        if ((ht & 31) == 0) PROF_T(11);
      }
      break;
    }
    spin_guard(++n);
    rs = ld_rlx4(rp);
  }
  __syncwarp();
}

template <int N, class F> __device__ __forceinline__ void check_tags(const uint4* gsrc, F off, uint32_t par, uint4* f) {
  int n = 0;
  while (true) {
    uint32_t bad = 0;
#pragma unroll
    for (int k = 0; k < N; k++) bad |= f[k].x ^ par;
    if (!(bad & 1u)) break;
#pragma unroll
    for (int k = 0; k < N; k++) f[k] = ld_rlx4(gsrc + off(k));
    spin_guard(++n);
  }
  __syncwarp();
}
template <int N> __device__ __forceinline__ void send_y(uint4* dst, uint32_t par, const float* acc) {
#pragma unroll
  for (int i = 0; i < N; i++) {
    const float* a = acc + 8 * i;
    st_rlx4(dst + i * 128, (pack2(a[0], a[1]) & ~1u) | par, pack2(a[2], a[3]), pack2(a[4], a[5]), pack2(a[6], a[7]));
  }
}
template <int N> __device__ __forceinline__ void retuple(float* a) {
#pragma unroll
  for (int i = 0; i < N; i++) asm volatile("mov.b32 %0, %1;" : "=f"(a[i]) : "f"(a[i]));
}

__device__ __forceinline__ int y_kblock(int rb, int h, int u) {
  if (u < 2) return 2 * rb + u;
  if (u >= 17) return 16 * h + 2 * ((u - 17) & 7) + ((u - 17) >> 3);
  const int e = u - 2;
  if (h != (rb >> 3)) return 16 * h + 2 * (e & 7) + (e >> 3);
  if (e == 14) return 16 * (h ^ 1) + 15;
  const int odd = e >= 7, f = e - 7 * odd;
  return 16 * h + 2 * (f < 3 ? (rb & 4) + f + (f >= (rb & 3)) : ((rb & 4) ^ 4) + f - 3) + odd;
}
__device__ __forceinline__ void prod_A(const Params& p, uint32_t sb, int pair, int rank) {
  const int c = rank, h = pair & 1, rb = pair >> 1, q = 2 * c + h;
  const int wq = __shfl_sync(0xffffffffu, (int)(threadIdx.x >> 5), 0), lane = threadIdx.x & 31;
  if (wq == 0) {
    const uint32_t epoch = load_epoch();
#pragma unroll 1
    for (int t = 4; t < 8; t++) {
      const int s = t & 3;
      const uint32_t full = sb + BAR_FULL + s * 8;
      mbar_wait(sb + BAR_EMPTY + s * 8, 0);
      if (elect_one()) {
        mbar_expect_tx(full, A_STG);
        tma_2d_mc(sb + s * A_STG + rank * 8192, &p.mX64, t * 64, rb * 128 + rank * 64, full);
        tma_2d(sb + s * A_STG + 16384, &p.mHre, t * 64, q * 128, full);
        tma_2d(sb + s * A_STG + 32768, &p.mHim, t * 64, q * 128, full);
        if (PF_S) tma_prefetch_2d(&p.mSre, (OWNA ? y_kblock(rb, h, s) : 16 * h + 2 * s) * 64, rb * 128 + rank * 64);
      }
    }
    uint32_t mask = 0;
    if (HOLD_S) mbar_wait(sb + BAR_P1, 0);
#pragma unroll 1
    for (int u = 0; u < 33; u++) {
      const int s = u & 3, r = u >= 17, kb = y_kblock(rb, h, u);
      const uint32_t full = sb + BAR_FULL + s * 8;
      mbar_wait(sb + BAR_EMPTY + s * 8, ((u >> 2) & 1) ^ 1);
      if (elect_one()) {
        mbar_expect_tx(full, u < 2 ? 16384 : A_STG);
        tma_2d_mc_stream(sb + s * A_STG + rank * 8192, r ? &p.mSim : &p.mSre, kb * 64, rb * 128 + rank * 64, full);
      }
      if (u < 2) continue;
      if (u == 16 || u == 17) mask = 0;
      wait_flags(mask, 3u << ((kb & 1) * 16 + (kb & 14)), &g_fab[(r * 2 + (lane >> 4)) * 64 + ((kb >> 4) * 8 + ((lane >> 1) & 7)) * 4 + 2 * c + (lane & 1)], epoch);
      if (u == 2 && lane == 0) PROF_T(8);
      if (elect_one()) {
        const uint8_t* src = g_ab + (size_t)((r * 32 + kb) * 4 + 2 * c) * 16384;
        bulk_g2s(sb + s * A_STG + 16384, src + (h ^ 1) * 16384, 16384, full);
        bulk_g2s(sb + s * A_STG + 32768, src + h * 16384, 16384, full);
        if (u == A1_N) mbar_arrive(sb + BAR_XFULL);
        if (u > PF_LAST && u < 30) tma_prefetch_2d(&p.mSim, y_kblock(rb, h, u + 3) * 64, rb * 128 + rank * 64);
      }
    }
  } else {
    const uint32_t epoch = load_epoch(), par = epoch & 1u;
    {
      const int ai = pair * 2 + rank, i4 = lane & 3;
      mbar_wait(sb + BAR_PUB, 0);
      if (threadIdx.x == 32) PROF_T(39);
      if (wq == 3) {
        float s0 = 0.f, s1 = 0.f;
        const uint32_t ra = sb + A_STAGING + (lane >> 1) * 1024 + (lane & 1) * 16;
#pragma unroll 1
        for (int t = 0; t < 32; t += 4) {
          uint4 v[4];
#pragma unroll
          for (int k = 0; k < 4; k++) v[k] = lds128(ra + ((t + k + (lane >> 1)) & 31) * 32);
          s0 += sum8(v[0]) + sum8(v[2]); s1 += sum8(v[1]) + sum8(v[3]);
        }
        s0 += s1; s0 += __shfl_xor_sync(0xffffffffu, s0, 1);
        if (!(lane & 1)) st_rlx(&g_hs[ai * 16 + (lane >> 1)], tagf(s0, par));
      } else {
        float cc[8] = {0.f, 0.f, 0.f, 0.f, 0.f, 0.f, 0.f, 0.f};
#pragma unroll 1
        for (int t = 0; t < 16; t += 4) {
          uint4 v[4];
#pragma unroll
          for (int k = 0; k < 4; k++) { const int row = (t + k) * 4 + i4; v[k] = lds128(sb + A_STAGING + 8192 + wq * 8192 + row * 128 + (((lane >> 2) ^ (row & 7)) << 4)); }
#pragma unroll
          for (int k = 0; k < 4; k++) colsum_add(cc, v[k]);
        }
        colsum_quad(cc, i4);
        if (wq == 2) sts64u(sb + OFF_RS + lane * 8, __float_as_uint(cc[0]), __float_as_uint(cc[1]));
        bar_sync(6, 64);
        if (wq == 1) {
          const float2 o = lds64(sb + OFF_RS + lane * 8);
          st_rlx2((uint2*)&g_ws[(ai / 22) * 1408 + (ai % 22) * 64 + lane * 2], tagf(cc[0] + o.x, par), tagf(cc[1] + o.y, par));
        }
      }
      bar_sync(3, 96);
      if (threadIdx.x == 32) PROF_T(29);
      if (GATHER_NS) __nanosleep(GATHER_NS);
    }
    gather<1>(sb, sb + A_EXT, threadIdx.x - 32, par, rb, g_hs, q * 128, 512 + q * 128, 128);
    if (wq <= 2 && elect_one()) {
      const int mb = wq - 1;
#pragma unroll 1
      for (int r = 0; r < 2; r++) {
        if (r == 0 && mb == 1) mbar_wait(sb + (A1_N >= 0 ? BAR_XFULL : BAR_P1), 0);
        uint8_t* dst = g_ab + (size_t)((r * 32 + 2 * rb + mb) * 4 + q) * 16384;
        uint32_t* flag = &g_fab[((r * 2 + mb) * 64 + rb * 4 + q) * FSTR];
        asm volatile("" : "+l"(dst), "+l"(flag));
        mbar_wait(sb + BAR_STQ + (r * 2 + mb) * 8, 0);
        if (r == 0 && mb == 0) PROF_T(16);
        fence_async_smem();
        if (r == 0 && mb == 0) PROF_T(18);
        const uint32_t piece = r ? PIECE : 16384;
#pragma unroll 1
        for (uint32_t o = 0; o < 16384; o += piece) {
          bulk_s2g(dst + o, sb + A_STAGING + mb * 16384 + o, piece);
          if (r) __nanosleep(PIECE_NS);
        }
        if (r == 0 && mb == 0) PROF_T(20);
        bulk_commit();
        bulk_wait_all();
        if (r == 0) mbar_arrive(sb + BAR_STGFREE + mb * 8);
        if (r == 0 && mb == 0) PROF_T(22);
        publish(flag, epoch);
        if (mb == 0 && r == 0) { mbar_arrive_n(sb + BAR_P1, 16); PROF_T(9); }
        if (mb == 1 && r == 0) PROF_T(21);
      }
    }
  }
}

__device__ __forceinline__ void ab_pack(uint32_t* v, const float* acc, float r0, float r1) {
#pragma unroll
  for (int i = 0; i < 32; i++) v[i] = pack2(acc[2 * i] * ((i & 1) ? r1 : r0), acc[2 * i + 1] * ((i & 1) ? r1 : r0));
}
__device__ __forceinline__ void ab_store(uint32_t a0, uint32_t sw, const uint32_t* v) {
#pragma unroll
  for (int g = 0; g < 16; g += 2) stsm4(a0 + (g >> 3) * 8192 + (((g & 7) ^ sw) << 4), v[2 * g], v[2 * g + 1], v[2 * g + 2], v[2 * g + 3]);
}

__device__ __forceinline__ void cons_A(const Params& p, uint32_t sb, int pair, int rank) {
  const int c = rank, h = pair & 1, rb = pair >> 1;
  const int w = __shfl_sync(0xffffffffu, (int)(threadIdx.x >> 7) - 1, 0), tid = threadIdx.x & 127, wq = __shfl_sync(0xffffffffu, tid >> 5, 0), lane = tid & 31;
  const uint64_t dk0 = desc_k(sb), dn0 = desc_n(sb), da0 = dk0 + w * 512;
  const uint32_t a0 = sb + A_STAGING + w * 16384 + (wq * 16 + (lane & 15)) * 128, sw = (lane >> 4) ^ (lane & 7);
  uint32_t bp[32];
  {
    float acc[128];
    zero_acc<128>(acc);
    if (LATE_CW) cluster_wait();
#pragma unroll 1
    for (int t = 0; t < 4; t++) {
      mbar_wait(sb + BAR_FULL + t * 8, 0);
      if (t == 0 && tid == 0) PROF_T(1 + w);
      wg_fence();
#pragma unroll
      for (int k = 0; k < 4; k++) wgmma_n256<0>(acc, da0 + t * (A_STG >> 4) + 2 * k, dk0 + t * (A_STG >> 4) + 1024 + 2 * k, 1);
      wg_commit();
      wg_wait<1>();
      if (t > 0) release(sb + BAR_EMPTY + (t - 1) * 8, lane, 1);
      const int wp = w * 4 + wq, i4 = lane & 3;
      if (!HPREP && t == PREP_WA - PREP_SPLIT) {
        mbar_wait(sb + BAR_PUB, 0);
        if (tid == 0 && w == 0) PROF_T(39);
        uint4 v[4];
#pragma unroll
        for (int k = 0; k < 4; k++) v[k] = lds128(sb + A_STAGING + (wp * 2 + (lane >> 4)) * 1024 + k * 256 + (lane & 15) * 16);
        float sh = (sum8(v[0]) + sum8(v[1])) + (sum8(v[2]) + sum8(v[3]));
#pragma unroll
        for (int o = 1; o < 16; o <<= 1) sh += __shfl_xor_sync(0xffffffffu, sh, o);
        if ((lane & 15) == 0) sts32(sb + OFF_RS + (wp * 2 + (lane >> 4)) * 4, sh);
      }
      if (!HPREP && t == PREP_WA) {
        uint4 v[4];
#pragma unroll
        for (int k = 0; k < 4; k++) { const int row = wp * 16 + k * 4 + i4; v[k] = lds128(sb + A_STAGING + 16384 + row * 128 + (((lane >> 2) ^ (row & 7)) << 4)); }
        float cc[8] = {0.f, 0.f, 0.f, 0.f, 0.f, 0.f, 0.f, 0.f};
#pragma unroll
        for (int k = 0; k < 4; k++) colsum_add(cc, v[k]);
        colsum_quad(cc, i4);
        sts64u(sb + A_EXT + wp * 256 + lane * 8, __float_as_uint(cc[0]), __float_as_uint(cc[1]));
        __syncwarp();
        if (lane == 0) mbar_arrive(sb + BAR_GATE);
      }
    }
    wg_wait<0>();
    release(sb + BAR_EMPTY + 24, lane, 1);
    if (tid == 0 && w == 0) PROF_T(32);
    retuple<128>(acc);
#pragma unroll 1
    for (int s = 0; s < 4; s++) {
      if (PRIO_A && s == 4 - PRIO_A && w == 1) bar_sync(2, 256);
      mbar_wait(sb + BAR_FULL + s * 8, 1);
      if (s == 3 && tid == 0 && w == 0) PROF_T(33);
      wg_fence();
#pragma unroll
      for (int k = 0; k < 4; k++) wgmma_n128<0>(acc, da0 + s * (A_STG >> 4) + 2 * k, dk0 + s * (A_STG >> 4) + 1024 + 2 * k, 1);
      wg_commit();
    }
    mbar_wait(sb + BAR_EXT, 0);
    const uint32_t rs0 = lds32u(sb + OFF_RS + (w * 64 + wq * 16 + (lane >> 2)) * 4), rs1 = lds32u(sb + OFF_RS + (w * 64 + wq * 16 + (lane >> 2) + 8) * 4);
    const uint4 ea = ext_frag(rs0, rs1, lane & 3, 0), eb = ext_frag(rs0, rs1, lane & 3, 1);
    wg_fence();
    wgmma_rs_n128<0>(acc, ea, desc_ext(sb + A_EXT), 1);
    wg_commit();
    if (PRIO_A && w == 0) bar_arrive(2, 256);
    const float r0 = rs_rstd(rs0), r1 = rs_rstd(rs1);
    wg_wait<0>();
    if (tid == 0 && w == 0) PROF_T(30);
    ab_pack(bp, acc, r0, r1);
    ab_store(a0, sw, bp);
    mbar_arrive(sb + BAR_STQ + w * 8);
    if (tid == 0 && w == 0) PROF_T(3);
    wg_fence();
    wgmma_rs_n128<0>(acc + 64, eb, desc_ext(sb + A_EXT), 1);
    wg_commit();
#pragma unroll 1
    for (int s = 0; s < 4; s++) {
      wg_fence();
#pragma unroll
      for (int k = 0; k < 4; k++) wgmma_n128<0>(acc + 64, da0 + s * (A_STG >> 4) + 2 * k, dk0 + s * (A_STG >> 4) + 2048 + 2 * k, 1);
      wg_commit();
      wg_wait<1>();
      if (s > 0) release(sb + BAR_EMPTY + (s - 1) * 8, lane, 1);
    }
    wg_wait<0>();
    release(sb + BAR_EMPTY + 24, lane, 1);
    if (tid == 0 && w == 0) PROF_T(31);
    ab_pack(bp, acc + 64, -r0, -r1);
    if (tid == 0 && w == 0) PROF_T(4);
  }
  float acc[128];
  zero_acc<128>(acc);
  constexpr int NST = 32 + OWNA;
  fence_async_smem();
  bar_sync(4, 256);
#pragma unroll 1
  for (int n = 0; n < 2; n++) {
    mbar_wait(sb + BAR_FULL + n * 8, 0);
    if (n == 0 && tid == 0 && w == 0) PROF_T(25);
    wg_fence();
#pragma unroll
    for (int k = 0; k < 4; k++) wgmma_n128<1>(acc + 64, da0 + n * (A_STG >> 4) + 2 * k, dn0 + (A_STAGING >> 4) + n * 1024 + 128 * k, 1);
    wg_commit();
    wg_wait<0>();
    release(sb + BAR_EMPTY + n * 8, lane, 1);
  }
  retuple<128>(acc);
  PROF_DECL(wt2);
#pragma unroll 1
  for (int n = 2 * OWNA; n < NST; n++) {
    const int s = n & 3;
    const bool pause = n == NST - SKEW_A && w == 1;
    if (pause) {
      wg_wait<0>();
      if (n <= NST - 4) release(sb + BAR_EMPTY + ((n - 1) & 3) * 8, lane, 1);
      bar_sync(1, 256);
    }
    PROF_W0();
    mbar_wait(sb + BAR_FULL + s * 8, (n >> 2) & 1);
    if (n > 0) PROF_W1(wt2);
    if (n == 2 * OWNA && tid == 0 && w == 0) PROF_T(5);
    if (n == 27 && tid == 0) { if (w == 0) { PROF_T(36); PROF_V(38, wt2); } }
    if (n == 8 && tid == 0 && w == 0) PROF_T(40);
    if (n == 16 && tid == 0 && w == 0) PROF_T(41);
    const uint64_t da = da0 + s * (A_STG >> 4), db = dn0 + s * (A_STG >> 4) + 1024;
    wg_fence();
#pragma unroll
    for (int k = 0; k < 4; k++) wgmma_n256<1>(acc, da + 2 * k, db + 128 * k, 1);
    wg_commit();
    if (n == NST - 1 && w == 0) bar_arrive(1, 256);
    if (n == 2 * OWNA + LATE_N && lane == 0) mbar_arrive(sb + BAR_GATE);
    if (n == 2 * OWNA + LATE_N + 3) {
      mbar_wait(sb + BAR_STGFREE + w * 8, 0);
      ab_store(a0, sw, bp);
      mbar_arrive(sb + BAR_STQ + (2 + w) * 8);
    }
    wg_wait<1>();
    if (n > 2 * OWNA && n <= NST - 4 && !pause) release(sb + BAR_EMPTY + ((n - 1) & 3) * 8, lane, 1);
  }
  const uint32_t par = (lds32u(sb + OFF_RS) >> 15) & 1u;
  wg_wait<0>();
  if (tid == 0) PROF_T(w ? 14 : 12);
  send_y<8>(g_yp + (size_t)(((rb * 4 + 2 * c + (OWNA ? h ^ 1 : 0)) * 2 + h) * 2 + w) * 1024 + tid, par, acc);
  send_y<8>(g_yp + (size_t)(((rb * 4 + 2 * c + (OWNA ? h : 1)) * 2 + h) * 2 + w) * 1024 + tid, par, acc + 64);
  if (tid == 0) PROF_T(w ? 17 : 13);
}

__device__ __forceinline__ void win_tile(const Params& p, uint32_t sb, int j, int v) {
  const bool z2 = v >= N0 && v < N0 + 8;
  const int kb = z2 ? v - N0 : v < N0 ? v : v - 8;
  const uint32_t full = sb + BAR_F1 + (v & 3) * 8;
  mbar_expect_tx(full, 24576);
#pragma unroll
  for (int i = 0; i < 3; i++) tma_2d(sb + B_W1 + (v & 3) * 24576 + i * 8192, &p.mWin, (z2 ? 688 : 0) + 176 * j + 64 * i, kb * 64, full);
}
__device__ __forceinline__ int g_kblock(int rb, int n) {
  if (n < 2) return 2 * rb + n;
  const int half = n >= 17, e = n - 2 - 15 * half;
  return 2 * (e >= 3 ? ((rb & 12) + 1 + e) & 15 : (rb & 12) + e + (e >= (rb & 3))) + half;
}
__device__ __forceinline__ void prod_B(const Params& p, uint32_t sb, int pair, int rank) {
  const int rb = pair >> 1, j = (pair & 1) * 2 + rank;
  const int tid = threadIdx.x, wq = __shfl_sync(0xffffffffu, tid >> 5, 0), lane = tid & 31;
  if (wq == 0) {
    const uint32_t epoch = load_epoch();
#pragma unroll 1
    for (int v = 4; v < 16; v++) {
      mbar_wait(sb + BAR_E1 + (v & 3) * 8, ((v >> 2) & 1) ^ 1);
      if (elect_one()) {
        win_tile(p, sb, j, v);
        if (PF_DIST && v >= 16 - PF_DIST && ((v ^ pair) & 1)) tma_prefetch_2d(&p.mWsp, g_kblock(rb, v - (16 - PF_DIST)) * 64, rb * 128 + rank * 64);
      }
    }
    uint32_t mask = 0;
    mbar_wait(sb + BAR_P1, 0);
#pragma unroll 1
    for (int n = 0; n < 32; n++) {
      const int s = n & 3, kb = g_kblock(rb, n);
      const bool own = OWNB && n < 2;
      const uint32_t full = sb + BAR_FULL + s * 8, st = sb + B_S0 + s * B_STG;
      mbar_wait(sb + BAR_EMPTY + s * 8, ((n >> 2) & 1) ^ 1);
      if (elect_one()) {
        mbar_expect_tx(full, own ? 16384 : B_STG);
        tma_2d_mc(st + rank * 8192, &p.mWsp, kb * 64, rb * 128 + rank * 64, full);
      }
      if (!own) wait_flags(mask, (1u << ((kb & 1) * 16 + (kb >> 1))) | (n == 20 ? 0x10001u << rb : 0u), &g_fz2[(j * 32 + lane) * FSTR], epoch);
      if (n == 2 * OWNB && lane == 0) PROF_T(8);
      if (elect_one()) {
        if (!own) bulk_g2s(st + 16384, g_z2 + (size_t)(kb * 4 + j) * 24576, 24576, full);
        if (n == 4 + OWNB + LATE_N) mbar_arrive(sb + BAR_STGFREE);
        if (n == 8) bulk_prefetch(p.wout + (rb * 4 + j) * 5504, 11008);
        const int m = n + PF_DIST;
        if (PF_DIST && m < 32 && ((n ^ pair) & 1)) tma_prefetch_2d(&p.mWsp, g_kblock(rb, m) * 64, rb * 128 + rank * 64);
      }
    }
    if (elect_one()) {
#pragma unroll 1
      for (int m = 0; m < 4; m++) {
        const uint32_t bar = sb + BAR_XFULL + m * 8, dst = sb + B_WO + m * 45056;
        mbar_wait(sb + BAR_EMPTY + m * 8, 1);
        mbar_expect_tx(bar, 45056);
        tma_2d(dst, &p.mWout, (j ^ 2 ^ (m & 2)) * 128, (j ^ (m & 1)) * 176, bar);
        tma_2d(dst + 22528, &p.mWout, (j ^ 2 ^ (m & 2)) * 128 + 64, (j ^ (m & 1)) * 176, bar);
      }
      mbar_wait(sb + BAR_PUB, 1);
      fence_async_smem();
      mbar_expect_tx(sb + BAR_XFULL + 48, 32768);
      tma_2d(sb, &p.mX, j * 128, rb * 128, sb + BAR_XFULL + 48);
      tma_2d(sb + 16384, &p.mX, j * 128 + 64, rb * 128, sb + BAR_XFULL + 48);
    }
  } else {
    const uint32_t epoch = load_epoch(), par = epoch & 1u;
    {
      float s = 0.f, q = 0.f, s2 = 0.f, q2 = 0.f;
      const uint32_t ra = sb + (j * 32 + lane) * 128, rx = (lane & 7) << 4;
#pragma unroll 1
      for (int hb = wq - 1; hb < 16; hb += 3) {
        mbar_wait(sb + BAR_XFULL + (hb >> 1) * 8, 0);
        uint4 v[4];
#pragma unroll
        for (int k = 0; k < 4; k++) v[k] = lds128(ra + (hb >> 1) * 16384 + ((((hb & 1) * 4 + k) << 4) ^ rx));
        acc_sq(v[0], s, q); acc_sq(v[1], s2, q2); acc_sq(v[2], s, q); acc_sq(v[3], s2, q2);
      }
      s += s2; q += q2;
      if (wq <= 2) sts64u(sb + B_RED + (wq - 1) * 256 + lane * 8, __float_as_uint(s), __float_as_uint(q));
      bar_sync(3, 96);
      if (wq == 3) {
        const float2 u = lds64(sb + B_RED + lane * 8), v = lds64(sb + B_RED + 256 + lane * 8);
        const float m = (s + (u.x + v.x)) * (1.f / 512.f);
        st_rlx(&g_rs[rb * 128 + j * 32 + lane], (pack2(std_ref(fmaf(q + (u.y + v.y), 1.f / 512.f, -m * m)), m) & 0xFFFF7FFFu) | (par << 15));
      }
    }
    if (tid == 96) PROF_T(10);
    if (GATHER_B) __nanosleep(GATHER_B);
    mbar_wait(sb + BAR_PUB, 0);
    gather<4>(sb, sb, tid - 32, par, rb, g_ws, 688 + 176 * j, 176 * j, 176);
    if (wq <= 2 && elect_one()) {
      const int mb = wq - 1;
      uint8_t* dst = g_z2 + (size_t)((2 * rb + mb) * 4 + j) * 24576;
      uint32_t* flag = &g_fz2[(j * 32 + mb * 16 + rb) * FSTR];
      asm volatile("" : "+l"(dst), "+l"(flag));
      mbar_wait(sb + BAR_STQ + mb * 8, 0);
      if (mb == 1) mbar_wait_idle(sb + BAR_STGFREE, 0);
      fence_async_smem();
#pragma unroll 1
      for (uint32_t o = 0, piece = mb ? PIECE : 8192; o < 24576; o += piece) {
        bulk_s2g(dst + o, sb + STG_B + (o >> 13) * 16384 + mb * 8192 + (o & 8191), piece);
        if (mb) __nanosleep(PIECE_NS / 2);
      }
      bulk_commit();
      bulk_wait_all();
      if (HGELU && mb == 1) mbar_arrive(sb + BAR_XFULL + 40);
      if (mb == 0) PROF_T(22);
      publish(flag, epoch);
      PROF_T(mb ? 21 : 9);
    }
    __syncwarp();
    mbar_wait_idle(sb + BAR_PUB, 1);
    fence_async_smem();
    const uint4* src = wq == 3 ? g_op + (size_t)(rb * 4 + j) * 2048 : g_yp + (size_t)((rb * 4 + j) * 2 + wq - 1) * 2048;
    const uint32_t* hp = (const uint32_t*)(src + ((lane >> 2) & 1) * 1024 + 7 * 128 + (lane & 3) * 32 + 31);
    int n = 0, w = 0;
    while (w < 2) {
      const uint32_t ok = __ballot_sync(0xffffffffu, ((ld_rlx(hp) ^ par) & 1u) == 0);
      while (w < 2 && ((ok >> (4 * w)) & 15u) == 15u) {
        if (elect_one()) {
          const uint32_t bar = sb + (wq == 3 ? BAR_UB + 16 + w * 8 : w ? BAR_STGFREE + 8 : BAR_FULL + 32);
          mbar_wait(sb + BAR_GATE, 1);
          mbar_expect_tx(bar, 16384);
          bulk_g2s_stream(sb + wq * 32768 + w * 16384, src + w * 1024, 16384, bar);
          if (wq != 2) PROF_T(wq == 3 ? (w ? 37 : 27) : w ? 26 : 25);
        }
        __syncwarp();
        w++;
      }
      spin_guard(++n);
      if (POLL_NS) __nanosleep(POLL_NS);
    }
  }
}

__device__ __forceinline__ uint4 ufrag(const float* v, const uint32_t* z) {
  return make_uint4(bmul2(z[0], pack2(v[0], v[1])), bmul2(z[1], pack2(v[2], v[3])), bmul2(z[2], pack2(v[4], v[5])), bmul2(z[3], pack2(v[6], v[7])));
}

__device__ __forceinline__ void cons_B(const Params& p, uint32_t sb, int pair, int rank) {
  const int rb = pair >> 1, j = (pair & 1) * 2 + rank;
  const int w = __shfl_sync(0xffffffffu, (int)(threadIdx.x >> 7) - 1, 0), tid = threadIdx.x & 127, wq = __shfl_sync(0xffffffffu, tid >> 5, 0), lane = tid & 31;
  const uint64_t dk0 = desc_k(sb), dn0 = desc_n(sb), da0 = dk0 + w * 512, dw0 = dn0 + (B_W1 >> 4);
  const uint32_t sw = (lane >> 4) ^ (lane & 7);
  const int i4 = lane & 3;
  uint16_t bs0, bs1;
  uint32_t z[44];
  float acc[88];
  {
    float a1[88], a2[88];
    zero_acc<88>(a1);
    if (LATE_CW) cluster_wait();
    float ps = 0.f, pq = 0.f;
    auto prep_rows = [&](int v) {
      const int t = 2 * (v - (PREP_V - 3));
      if (HPREP) { if (t == 6 && lane == 0) mbar_arrive(sb + BAR_GATE); } else
      if (t >= 0 && t < 8) {
        const uint32_t ra = sb + (j * 32 + (w * 4 + wq) * 4 + (lane >> 3)) * 128 + (lane & 7) * 16 + t * 16384;
        mbar_wait(sb + BAR_XFULL + t * 8, 0); mbar_wait(sb + BAR_XFULL + t * 8 + 8, 0);
        const uint4 v0 = lds128(ra), v1 = lds128(ra + 16384);
        acc_sq(v0, ps, pq); acc_sq(v1, ps, pq);
        if (t == 6) {
          sts64u(sb + B_RED + ((lane & 7) * 32 + (w * 4 + wq) * 4 + (lane >> 3)) * 8, __float_as_uint(ps), __float_as_uint(pq));
          __syncwarp();
          if (lane == 0) mbar_arrive(sb + BAR_GATE);
        }
      }
    };
#pragma unroll 1
    for (int v = 0; v < N0; v++) {
      mbar_wait(sb + BAR_XFULL + v * 8, 0);
      mbar_wait(sb + BAR_F1 + (v & 3) * 8, (v >> 2) & 1);
      if (v == 0 && tid == 0) PROF_T(1 + w);
      wg_fence();
#pragma unroll
      for (int k = 0; k < 4; k++) wgmma_n176<1>(a1, da0 + v * 1024 + 2 * k, dw0 + (v & 3) * 1536 + 128 * k, 1);
      wg_commit();
      wg_wait<1>();
      if (v > 0 && lane == 0) mbar_arrive(sb + BAR_E1 + ((v - 1) & 3) * 8);
      if (PREP_V - 3 < N0) prep_rows(v);
    }
#pragma unroll
    for (int i = 0; i < 88; i++) asm volatile("mov.b32 %0, 0;" : "=f"(a2[i]));
#pragma unroll 1
    for (int i = 0; i < 8; i++) {
      const int v = N0 + i;
      mbar_wait(sb + BAR_XFULL + i * 8, 0);
      mbar_wait(sb + BAR_F1 + (v & 3) * 8, (v >> 2) & 1);
      if (i == 7 && tid == 0 && w == 0) PROF_T(32);
      wg_fence();
#pragma unroll
      for (int k = 0; k < 4; k++) wgmma_n176<1>(a2, da0 + i * 1024 + 2 * k, dw0 + (v & 3) * 1536 + 128 * k, 1);
      wg_commit();
      wg_wait<1>();
      if (lane == 0) mbar_arrive(sb + BAR_E1 + ((v - 1) & 3) * 8);
      prep_rows(v);
      if (i == (!HPREP && PREP_V > N0 + 1 ? PREP_V - N0 : 1) && lane == 0) mbar_arrive(sb + BAR_PUB);
    }
    mbar_wait(sb + BAR_EXT, 0);
    const uint32_t rs0 = lds32u(sb + OFF_RS + (w * 64 + wq * 16 + (lane >> 2)) * 4), rs1 = lds32u(sb + OFF_RS + (w * 64 + wq * 16 + (lane >> 2) + 8) * 4);
    const int zskip = MIDREL ? (w ? N0 + 4 : N0 + 1) : -1;
    auto z1_step = [&](int i) {
      mbar_wait(sb + BAR_F1 + (i & 3) * 8, ((i + 8) >> 2) & 1);
      wg_fence();
#pragma unroll
      for (int k = 0; k < 4; k++) wgmma_n176<1>(a1, da0 + i * 1024 + 2 * k, dw0 + (i & 3) * 1536 + 128 * k, 1);
      wg_commit();
      wg_wait<1>();
      if (lane == 0 && i != zskip) mbar_arrive(sb + BAR_E1 + ((i - 1) & 3) * 8);
    };
    int zi = N0;
    {
      const uint4 e2 = ext_frag(rs0, rs1, i4, 0), e1 = ext_frag(rs0, rs1, i4, 1);
      wg_fence();
      wgmma_rs_n176<0>(a2, e2, desc_ext(sb), 1);
      wgmma_rs_n176<0>(a1, e1, desc_ext(sb), 1);
      wg_commit();
      const uint16_t* bp = (const uint16_t*)p.bsp + rb * 128 + w * 64 + wq * 16 + (lane >> 2);
      asm volatile("ld.global.nc.u16 %0, [%1];" : "=h"(bs0) : "l"(bp));
      asm volatile("ld.global.nc.u16 %0, [%1];" : "=h"(bs1) : "l"(bp + 8));
#pragma unroll 1
      do { z1_step(zi); } while (++zi < (w ? N0 + 4 : N0 + 1));
    }
    if (STG_B == 0 && w == 1) bar_arrive(5, 256);
    if (tid == 0 && w == 0) PROF_T(30);
    const float h0 = 0.5f * rs_rstd(rs0), h1 = 0.5f * rs_rstd(rs1);
    const uint32_t par = (rs0 >> 15) & 1u;
    uint32_t* ex = (uint32_t*)&g_ln2[rb * 512 + w * 64 + wq * 16 + (lane >> 2)];
    {
      float s0 = 0.f, q0 = 0.f, s1 = 0.f, q1 = 0.f;
#pragma unroll
      for (int g = 0; g < 11; g++) {
        float e[8];
#pragma unroll
        for (int k = 0; k < 8; k++) e[k] = gelu_h(a2[g * 8 + k] * ((k & 2) ? h1 : h0));
        s0 += (e[0] + e[1]) + (e[4] + e[5]); s1 += (e[2] + e[3]) + (e[6] + e[7]);
        q0 = fmaf(e[0], e[0], fmaf(e[1], e[1], fmaf(e[4], e[4], fmaf(e[5], e[5], q0))));
        q1 = fmaf(e[2], e[2], fmaf(e[3], e[3], fmaf(e[6], e[6], fmaf(e[7], e[7], q1))));
        z[4 * g] = pack2(e[0], e[1]); z[4 * g + 1] = pack2(e[2], e[3]); z[4 * g + 2] = pack2(e[4], e[5]); z[4 * g + 3] = pack2(e[6], e[7]);
        if (MIDREL && g == MIDREL) { asm volatile("" : "+f"(q0), "+f"(q1)); wg_wait<0>(); if (lane == 0) mbar_arrive(sb + BAR_E1 + ((zi - 1) & 3) * 8); }
      }
      const bool u1 = i4 & 1, u2 = i4 & 2;
      const float e0 = (u2 ? q0 : s0) + __shfl_xor_sync(0xffffffffu, u2 ? s0 : q0, 2);
      const float e1 = (u2 ? q1 : s1) + __shfl_xor_sync(0xffffffffu, u2 ? s1 : q1, 2);
      st_rlx(ex + (j * 128 + (i4 & 1) * 8) * 2 + (i4 >> 1), tagf((u1 ? e1 : e0) + __shfl_xor_sync(0xffffffffu, u1 ? e0 : e1, 1), par));
    }
    if (tid == 0 && w == 0) PROF_T(12);
    uint2 pa = make_uint2(~par, 0), pb = pa;
#pragma unroll 1
    do {
      if (EARLY_ST && zi == (w ? STAG1 : STAG0) - EARLY_ST) { pa = ld_rlx2((const uint2*)ex + i4 * 128); pb = ld_rlx2((const uint2*)ex + i4 * 128 + 8); }
      z1_step(zi);
    } while (++zi < (w ? STAG1 : STAG0));
    {
      int n = 0;
      while (((pa.x ^ par) | (pa.y ^ par) | (pb.x ^ par) | (pb.y ^ par)) & 1u) {
        pa = ld_rlx2((const uint2*)ex + i4 * 128); pb = ld_rlx2((const uint2*)ex + i4 * 128 + 8);
        spin_guard(++n);
      }
      __syncwarp();
      if (tid == 0 && w == 0) PROF_T(13);
      float m0 = __uint_as_float(pa.x), m1 = __uint_as_float(pb.x), q0 = __uint_as_float(pa.y), q1 = __uint_as_float(pb.y);
#pragma unroll
      for (int o = 1; o < 4; o <<= 1) {
        m0 += __shfl_xor_sync(0xffffffffu, m0, o); q0 += __shfl_xor_sync(0xffffffffu, q0, o);
        m1 += __shfl_xor_sync(0xffffffffu, m1, o); q1 += __shfl_xor_sync(0xffffffffu, q1, o);
      }
      m0 *= (1.f / 688.f); m1 *= (1.f / 688.f);
      const float r0 = rstd_ref(fmaf(q0, 1.f / 688.f, -m0 * m0)), r1 = rstd_ref(fmaf(q1, 1.f / 688.f, -m1 * m1));
      const uint32_t n0 = pack2(-m0, -m0), n1 = pack2(-m1, -m1), c0 = pack2(r0, r0), c1 = pack2(r1, r1);
      const uint32_t a0 = sb + STG_B + (w * 64 + wq * 16 + (lane & 15)) * 128;
      if (STG_B == 0 && w == 0) bar_sync(5, 256);
      static_assert(N0 + NS >= 3, "x tiles 1..3 must be dead");
      static_assert(!STAG || STAG0 >= (STG_B ? 4 : 3), "staging");
      if (STAG ? STAG0 < (STG_B ? 5 : 4) : N0 + NS < 4) wg_wait<0>();
#pragma unroll
      for (int g = 0; g < 22; g += 2)
        stsm4(a0 + (g >> 3) * 16384 + (((g & 7) ^ sw) << 4), bmul2(badd2(z[2 * g], n0), c0), bmul2(badd2(z[2 * g + 1], n1), c1),
              bmul2(badd2(z[2 * g + 2], n0), c0), bmul2(badd2(z[2 * g + 3], n1), c1));
      mbar_arrive(sb + BAR_STQ + w * 8);
      if (tid == 0 && w == 0) PROF_T(20);
    }
#pragma unroll 1
    do { z1_step(zi); } while (++zi < 8);
    wg_wait<0>();
    release(sb + BAR_P1, lane, 1);
    if (OWNB) fence_async_smem();
    if (tid == 0 && w == 0) PROF_T(31);
#pragma unroll
    for (int k = 0; k < 44; k++) {
      const float e0 = a1[2 * k] * ((k & 1) ? h1 : h0), e1 = a1[2 * k + 1] * ((k & 1) ? h1 : h0);
      z[k] = HGELU ? pack2(e0, e1) : pack2(gelu_h(e0), gelu_h(e1));
    }
    if (j == 3) { z[40] = 0; z[41] = 0; z[42] = 0; z[43] = 0; }
  }
  if (tid == 0) PROF_T(3 + w);
  uint4 uf[11];
  uint32_t par;
  {
    const uint64_t dg0 = da0 + (B_S0 >> 4), dz0 = dn0 + (B_S0 >> 4) + 1024;
    {
      const float b0 = __uint_as_float((uint32_t)bs0 << 16), b1 = __uint_as_float((uint32_t)bs1 << 16);
#pragma unroll
      for (int i = 0; i < 88; i++) asm volatile("mov.b32 %0, %1;" : "=f"(acc[i]) : "f"((i & 2) ? b1 : b0));
    }
    PROF_DECL(wt2);
    const uint32_t za = sb + w * 22528 + tid * 16; (void)za;
    if (OWNB && !PEEL) bar_sync(4, 256);
#pragma unroll 1
    for (int n = PEEL ? 2 : 0; n < 32; n++) {
      const int s = n & 3;
      const bool pause = n == 32 - SKEW_B && w == 1;
      if (pause) {
        wg_wait<0>();
        release(sb + BAR_EMPTY + ((n - 1) & 3) * 8, lane, 1);
        bar_sync(2, 256);
      }
      PROF_W0();
      mbar_wait(sb + BAR_FULL + s * 8, (n >> 2) & 1);
      if (n > 0) PROF_W1(wt2);
      if (n == 0 && tid == 0 && w == 0) PROF_T(5);
      if (n == 27 && tid == 0) { if (w == 0) { PROF_T(36); PROF_V(38, wt2); } }
      if (n == 8 && tid == 0 && w == 0) PROF_T(40);
      if (n == 16 && tid == 0 && w == 0) PROF_T(41);
      if (n == 2 && tid == 0 && w == 0) PROF_T(39);
      const uint64_t db = OWNB && !PEEL && n < 2 ? dn0 + (512ull << 16) + (STG_B >> 4) + n * 512 : dz0 + s * (B_STG >> 4);
      wg_fence();
#pragma unroll
      for (int k = 0; k < 4; k++) wgmma_n176<1>(acc, dg0 + s * (B_STG >> 4) + 2 * k, db + 128 * k, 1);
      wg_commit();
      if (n == 31) bar_arrive(2 - w, 256);
      wg_wait<1>();
      if (n > 0 && !pause) release(sb + BAR_EMPTY + ((n - 1) & 3) * 8, lane, 1);
      if (HGELU && n == Z_IN) {
        mbar_wait(sb + BAR_EXT, 1);
#pragma unroll
        for (int k = 0; k < 11; k++) { const uint4 v = lds128(za + k * 2048); z[4 * k] = v.x; z[4 * k + 1] = v.y; z[4 * k + 2] = v.z; z[4 * k + 3] = v.w; }
        __syncwarp();
      }
      if (HGELU && n == Z_OUT) {
        mbar_wait(sb + BAR_XFULL + 40, 1);
#pragma unroll
        for (int k = 0; k < 11; k++) sts128(za + k * 2048, make_uint4(z[4 * k], z[4 * k + 1], z[4 * k + 2], z[4 * k + 3]));
        mbar_arrive(sb + BAR_STQ + (2 + w) * 8);
      }
    }
    par = (lds32u(sb + OFF_RS) >> 15) & 1u;
    wg_wait<0>();
    release(sb + BAR_EMPTY + 24, lane, 1);
    if (tid == 0) PROF_T(w ? 14 : 42);
#pragma unroll
    for (int k = 0; k < 11; k++) uf[k] = ufrag(acc + 8 * k, z + 4 * k);
  }
  float oc[64];
  zero_acc<64>(oc);
  {
    const uint32_t ua = sb + w * 22528 + tid * 16;
    {
      const uint32_t ud = map_peer(ua, rank ^ 1), ubar = map_peer(sb + BAR_UB + w * 8, rank ^ 1);
#pragma unroll
      for (int k = 0; k < 11; k++) st_async4(ud + k * 2048, uf[k], ubar);
    }
    uint4 pf[11];
    const uint64_t dw = dn0 + (896ull << 16) + (B_WO >> 4);
#pragma unroll
    for (int ch = 0; ch < 2; ch++) {
      bar_sync(1 + w, 256);
      mbar_wait(sb + BAR_XFULL + ch * 16, 1);
      wg_fence();
#pragma unroll
      for (int k = 0; k < 11; k++) wgmma_rs_n128<1>(oc, uf[k], dw + ch * 5632 + 128 * k, k ? 1 : w >> 1);
      if (ch == 0) {
        mbar_wait_cluster(sb + BAR_UB + w * 8, 0);
        if (tid == 0) PROF_T(w ? 16 : 33);
#pragma unroll
        for (int k = 0; k < 11; k++) pf[k] = lds128(ua + k * 2048);
        __syncwarp();
        if (lane == 0) mbar_arrive(sb + BAR_PUB);
      }
      mbar_wait(sb + BAR_XFULL + ch * 16 + 8, 1);
      wg_fence();
#pragma unroll
      for (int k = 0; k < 11; k++) wgmma_rs_n128<1>(oc, pf[k], dw + ch * 5632 + 2816 + 128 * k, 1);
      wg_commit();
      if (!(w & ch)) bar_arrive(2 - w, 256);
      wg_wait<0>();
      if (ch == 0) {
        if (lane == 0) mbar_arrive(sb + BAR_GATE);
        if (tid == 0) PROF_T(w ? 28 : 43);
        send_y<8>(g_op + (size_t)((rb * 4 + (j ^ 2)) * 2 + w) * 1024 + tid, par, oc);
      }
    }
  }
  if (tid == 0) PROF_T(w ? 7 : 34);
  {
    const uint32_t a0 = sb + (w * 64 + wq * 16 + (lane & 15)) * 128, ta = sb + w * 16384 + tid * 16;
    const uint4* ysrc = g_yp + (size_t)(rb * 4 + j) * 4096 + w * 1024 + tid;
    const uint4* osrc = g_op + (size_t)(rb * 4 + j) * 2048 + w * 1024 + tid;
    auto off = [](int k) { return k * 128; };
    mbar_wait(sb + BAR_UB + 16 + w * 8, 0);
    if (tid == 0 && w) PROF_T(35);
#pragma unroll
    for (int hf = 0; hf < 2; hf++) {
      uint4 op[4], y0[4], y1[4];
      uint32_t gt[16], x[16];
#pragma unroll
      for (int k = 0; k < 4; k++) op[k] = lds128(ta + 98304 + (hf * 4 + k) * 2048);
      check_tags<4>(osrc + hf * 512, off, par, op);
#pragma unroll
      for (int i = 0; i < 4; i++) {
        const float* o = oc + hf * 32 + 8 * i;
        gt[4 * i] = pack2(silu_f(o[0] + bf_lo(op[i].x)), silu_f(o[1] + bf_hi(op[i].x))); gt[4 * i + 1] = pack2(silu_f(o[2] + bf_lo(op[i].y)), silu_f(o[3] + bf_hi(op[i].y)));
        gt[4 * i + 2] = pack2(silu_f(o[4] + bf_lo(op[i].z)), silu_f(o[5] + bf_hi(op[i].z))); gt[4 * i + 3] = pack2(silu_f(o[6] + bf_lo(op[i].w)), silu_f(o[7] + bf_hi(op[i].w)));
      }
      if (hf == 0) {
        if (tid == 0 && w) PROF_T(24);
        mbar_wait(sb + BAR_XFULL + 48, 1);
        mbar_wait(sb + (w ? BAR_STGFREE + 8 : BAR_FULL + 32), 0);
        if (tid == 0 && w) PROF_T(2);
      }
#pragma unroll
      for (int k = 0; k < 4; k++) {
        y0[k] = lds128(ta + 32768 + (hf * 4 + k) * 2048); y1[k] = lds128(ta + 65536 + (hf * 4 + k) * 2048);
        ldsm4(a0 + hf * 16384 + (((2 * k) ^ sw) << 4), x[4 * k], x[4 * k + 1], x[4 * k + 2], x[4 * k + 3]);
      }
      check_tags<4>(ysrc + hf * 512, off, par, y0);
      check_tags<4>(ysrc + 2048 + hf * 512, off, par, y1);
#pragma unroll
      for (int i = 0; i < 4; i++)
        stsm4(a0 + hf * 16384 + (((2 * i) ^ sw) << 4), bfma2(badd2(y0[i].x, y1[i].x), gt[4 * i], x[4 * i]), bfma2(badd2(y0[i].y, y1[i].y), gt[4 * i + 1], x[4 * i + 1]),
              bfma2(badd2(y0[i].z, y1[i].z), gt[4 * i + 2], x[4 * i + 2]), bfma2(badd2(y0[i].w, y1[i].w), gt[4 * i + 3], x[4 * i + 3]));
      fence_async_smem();
      __syncwarp();
      if (elect_one()) { tma_store_2d(&p.mOut, j * 128 + hf * 64, rb * 128 + w * 64 + wq * 16, sb + hf * 16384 + (w * 64 + wq * 16) * 128); bulk_commit(); }
    }
    bulk_wait_read();
    if (tid == 0) PROF_T(w ? 17 : 18);
  }
}

__device__ __forceinline__ void first_loads(const Params& p, uint32_t sb, bool isA, int pair, int rank, int t0, int t1) {
    const int rb = pair >> 1;
    if (isA) {
#pragma unroll 1
      for (int t = t0; t < t1; t++) {
        const uint32_t full = sb + BAR_FULL + t * 8;
        mbar_expect_tx(full, A_STG);
        tma_2d(sb + t * A_STG, &p.mX, t * 64, rb * 128, full);
        tma_2d(sb + t * A_STG + 16384, &p.mHre, t * 64, (2 * rank + (pair & 1)) * 128, full);
        tma_2d(sb + t * A_STG + 32768, &p.mHim, t * 64, (2 * rank + (pair & 1)) * 128, full);
      }
    } else {
#pragma unroll 1
      for (int t = t0; t < t1; t++) {
        mbar_expect_tx(sb + BAR_XFULL + t * 8, 16384);
        tma_2d(sb + t * 16384, &p.mX, t * 64, rb * 128, sb + BAR_XFULL + t * 8);
        win_tile(p, sb, (pair & 1) * 2 + rank, t);
      }
    }
}

__global__ void __launch_bounds__(384, 1) fused_kernel(const __grid_constant__ Params p) {
  extern __shared__ __align__(1024) uint8_t smem[];
  const uint32_t sb = (uint32_t)__cvta_generic_to_shared(smem);
  if (CFIRST ? blockIdx.x < 4 : blockIdx.x >= 128) { role_C(p, sb); return; }
  const int li_ = blockIdx.x >> 1;
  const int cl = p.cmap[li_];
  const int rank = blockIdx.x & 1, pair = cl >> 1;
  const bool isA = (cl & 1) == 0;
  const int warp = __shfl_sync(0xffffffffu, (int)(threadIdx.x >> 5), 0);
  if (warp == 0) {
   if (elect_one()) {
    PROF_T(0);
#pragma unroll
    for (int i = 0; i < 5; i++) mbar_init(sb + BAR_FULL + i * 8, i == 4 ? 2 : 1);
#pragma unroll
    for (int i = 0; i < 12; i++) mbar_init(sb + BAR_XFULL + i * 8, 1);
    asm volatile("fence.mbarrier_init.release.cluster;" ::: "memory");
    fence_async_smem();
    first_loads(p, sb, isA, pair, rank, 0, PRO_T0);
   }
  } else if (warp == 1 && elect_one()) {
    spin_guard((sb & 1023) ? SPIN_LIMIT + 1 : 0);
#pragma unroll
    for (int i = 0; i < 5; i++) mbar_init(sb + BAR_EMPTY + i * 8, 16);
#pragma unroll
    for (int i = 0; i < 4; i++) { mbar_init(sb + BAR_E1 + i * 8, 8); mbar_init(sb + BAR_STQ + i * 8, 128); mbar_init(sb + BAR_UB + i * 8, 1); }
    mbar_expect_tx(sb + BAR_UB, 22528); mbar_expect_tx(sb + BAR_UB + 8, 22528);
    mbar_init(sb + BAR_STGFREE, 1); mbar_init(sb + BAR_STGFREE + 8, isA ? 1 : 2); mbar_init(sb + BAR_P1, 16);
    sts32(sb + OFF_CLAIM, 0.f);
    mbar_init(sb + BAR_EXT, 128); mbar_init(sb + BAR_GATE, 8); mbar_init(sb + BAR_PUB, isA ? 1 : 8);
    asm volatile("fence.mbarrier_init.release.cluster;" ::: "memory");
    fence_async_smem();
  }
  __syncthreads();
  cluster_arrive();
  if (warp < 4) {
    asm volatile("setmaxnreg.dec.sync.aligned.u32 " REG_LO ";");
    if (PRO_T0 < PRO_T) { if (warp == 0 && elect_one()) first_loads(p, sb, isA, pair, rank, PRO_T0, PRO_T); __syncwarp(); }
    cluster_wait();
    if (warp == 0 && elect_one()) {
      const int rb = pair >> 1;
      if (isA) {
        const int ai = pair * 2 + rank;
        mbar_expect_tx(sb + BAR_PUB, 32768);
        bulk_g2s(sb + A_STAGING, (ai < 32 ? p.hre : p.him) + (ai & 31) * 8192, 16384, sb + BAR_PUB);
        tma_2d(sb + A_STAGING + 16384, &p.mWin, (ai % 22) * 64, (ai / 22) * 128, sb + BAR_PUB);
        tma_2d(sb + A_STAGING + 24576, &p.mWin, (ai % 22) * 64, (ai / 22) * 128 + 64, sb + BAR_PUB);
#pragma unroll 1
        for (int t = PRO_T; t < 4; t++) {
          const uint32_t full = sb + BAR_FULL + t * 8;
          mbar_expect_tx(full, A_STG);
          tma_2d_mc(sb + t * A_STG + rank * 8192, &p.mX64, t * 64, rb * 128 + rank * 64, full);
          tma_2d(sb + t * A_STG + 16384, &p.mHre, t * 64, (2 * rank + (pair & 1)) * 128, full);
          tma_2d(sb + t * A_STG + 32768, &p.mHim, t * 64, (2 * rank + (pair & 1)) * 128, full);
        }
      } else {
#pragma unroll 1
        for (int t = PRO_T; t < 8; t++) {
          if (!XFIRST && t < 4) win_tile(p, sb, (pair & 1) * 2 + rank, t);
          mbar_expect_tx(sb + BAR_XFULL + t * 8, 16384);
          tma_2d_mc(sb + t * 16384 + rank * 8192, &p.mX64, t * 64, rb * 128 + rank * 64, sb + BAR_XFULL + t * 8);
        }
        if (XFIRST) for (int t = PRO_T; t < 4; t++) win_tile(p, sb, (pair & 1) * 2 + rank, t);
      }
    }
    __syncwarp();
    if (isA) prod_A(p, sb, pair, rank); else prod_B(p, sb, pair, rank);
  } else {
    asm volatile("setmaxnreg.inc.sync.aligned.u32 " REG_HI ";");
    if (!LATE_CW) cluster_wait();
    if (isA) cons_A(p, sb, pair, rank); else cons_B(p, sb, pair, rank);
  }
  __syncwarp();
  cluster_arrive();
  cluster_wait();
  if (threadIdx.x == 0) asm volatile("red.relaxed.gpu.global.add.u32 [%0], 1;" ::"l"(&g_epoch[blockIdx.x]) : "memory");
}

typedef CUresult (*EncFn)(CUtensorMap*, CUtensorMapDataType, cuuint32_t, void*, const cuuint64_t*, const cuuint64_t*, const cuuint32_t*,
                          const cuuint32_t*, CUtensorMapInterleave, CUtensorMapSwizzle, CUtensorMapL2promotion, CUtensorMapFloatOOBfill);

void make_map(EncFn enc, CUtensorMap* m, const void* ptr, uint64_t cols, uint64_t rows, uint32_t box_c, uint32_t box_r) {
  cuuint64_t gd[2] = {cols, rows}; cuuint64_t gs[1] = {cols * 2}; cuuint32_t bd[2] = {box_c, box_r}; cuuint32_t es[2] = {1, 1};
  enc(m, CU_TENSOR_MAP_DATA_TYPE_BFLOAT16, 2, const_cast<void*>(ptr), gd, gs, bd, es, CU_TENSOR_MAP_INTERLEAVE_NONE, CU_TENSOR_MAP_SWIZZLE_128B,
      cols == 2048 ? PROMO : PROMO1, CU_TENSOR_MAP_FLOAT_OOB_FILL_NONE);
}

}

extern "C" void kernel_launch(void* const* d_in, const int* in_sizes, int n_in, void* d_out, int out_size) {
  (void)in_sizes; (void)n_in; (void)out_size;
  static EncFn enc = nullptr;
  if (!enc) {
    void* fn = nullptr; cudaDriverEntryPointQueryResult qr;
    cudaGetDriverEntryPoint("cuTensorMapEncodeTiled", &fn, cudaEnableDefault, &qr);
    enc = (EncFn)fn;
    cudaFuncSetAttribute(fused_kernel, cudaFuncAttributeMaxDynamicSharedMemorySize, SMEM_TOTAL);
  }
  Params p;
  make_map(enc, &p.mX, d_in[0], 512, 2048, 64, 128);
  make_map(enc, &p.mX64, d_in[0], 512, 2048, 64, 64);
  make_map(enc, &p.mSre, d_in[1], 2048, 2048, 64, 64);
  make_map(enc, &p.mSim, d_in[2], 2048, 2048, 64, 64);
  make_map(enc, &p.mHre, d_in[3], 512, 512, 64, 128);
  make_map(enc, &p.mHim, d_in[4], 512, 512, 64, 128);
  make_map(enc, &p.mWin, d_in[6], 1376, 512, 64, 64);
  make_map(enc, &p.mWsp, d_in[7], 2048, 2048, 64, 64);
  make_map(enc, &p.mWout, d_in[9], 512, 688, 64, 176);
  make_map(enc, &p.mOut, d_out, 512, 2048, 64, 16);
  p.x = (const __nv_bfloat16*)d_in[0]; p.hre = (const __nv_bfloat16*)d_in[3]; p.him = (const __nv_bfloat16*)d_in[4];
  p.win = (const __nv_bfloat16*)d_in[6]; p.bsp = (const __nv_bfloat16*)d_in[8]; p.wout = (const __nv_bfloat16*)d_in[9];
  {
    int order[64], n = 0;
    if (CMAP) {
      for (int pos = 0; pos < 8; pos++) for (int r = 0; r < 4; r++) order[n++] = 4 + r * 8 + pos;
      for (int pos = 0; pos < 7; pos++) for (int r = 0; r < 4; r++) order[n++] = 36 + r * 7 + pos;
      for (int i = 0; i < 4; i++) order[n++] = CFIRST ? (i < 2 ? 2 + i : 62 + i) : i;
      static const int sp1[16] = {0, 1, 2, 3, 0, 1, 2, 3, 1, 0, 3, 2, 1, 0, 3, 2}, sp2[16] = {0, 0, 2, 2, 1, 1, 3, 3, 0, 0, 2, 1, 1, 3, 3, 2};
      static const int sp3[16] = {0, 0, 2, 2, 1, 1, 1, 1, 0, 0, 2, 3, 3, 3, 3, 2}, sp4[16] = {0, 0, 0, 0, 1, 1, 1, 1, 2, 2, 2, 3, 3, 3, 3, 2},
        sp5[16] = {1, 1, 0, 1, 1, 0, 0, 0, 3, 3, 3, 3, 2, 2, 2, 2}, sp6[16] = {1, 0, 0, 1, 0, 1, 0, 1, 3, 2, 3, 2, 3, 2, 3, 2};
      const int* sp = CMAP == 2 ? sp2 : CMAP == 3 ? sp3 : CMAP == 4 ? sp4 : CMAP == 5 ? sp5 : CMAP == 6 ? sp6 : sp1;
      int cnt[4] = {0, 0, 0, 0};
      for (int g = 0; g < 16; g++) for (int r = 0; r < 4; r++) { const int s = sp[g]; p.cmap[order[g * 4 + r]] = (uint8_t)((cnt[s]++ << 2) | s); }
    } else {
      for (int i = 0; i < 64; i++) p.cmap[i] = (uint8_t)i;
    }
  }
  cudaLaunchConfig_t cfg = {};
  cfg.gridDim = dim3(132); cfg.blockDim = dim3(384); cfg.dynamicSmemBytes = SMEM_TOTAL; cfg.stream = cudaStreamPerThread;
  cudaLaunchAttribute at[1];
  at[0].id = cudaLaunchAttributeClusterDimension; at[0].val.clusterDim.x = 2; at[0].val.clusterDim.y = 1; at[0].val.clusterDim.z = 1;
  cfg.attrs = at; cfg.numAttrs = 1;
  cudaLaunchKernelEx(&cfg, fused_kernel, p);
}
```
